```python
import torch

def _softmax(x, axis=-1):
    return torch.softmax(x, dim=axis)

def _gelu(x):
    return torch.nn.functional.gelu(x, approximate='tanh')

def _silu(x):
    return torch.nn.functional.silu(x)

def _sigmoid(x):
    return torch.sigmoid(x)

def _layernorm(x, axis=-1, eps=1e-05):
    m = x.mean(dim=axis, keepdim=True)
    v = x.var(dim=axis, keepdim=True, unbiased=False)
    return (x - m) / torch.sqrt(v + eps)

def _scatter_add(tgt, idx, src, axis=0):
    return tgt.clone().index_add_(axis, idx, src)

def _segment_sum(src, seg, n):
    out = torch.zeros((n,) + src.shape[1:], dtype=src.dtype)
    return out.index_add_(0, seg, src)

def _pad(x, pw):
    flat = tuple((v for pair in reversed(pw) for v in pair))
    return torch.nn.functional.pad(x, flat)
kernel_name = 'adaLN_cond__compressed_kv_cla__swiglu_ffn__decode'

def setup_inputs():

    _w = lambda a: (lambda t: t.to(torch.bfloat16) if t.is_floating_point() else t)(torch.as_tensor(a))

    def _A_setup():
        B, H, Sq, Sk, D, M = (4, 32, 1, 4096, 128, 576)
        Dc = 4 * D
        return {'x': _w((lambda *s: torch.randn(*s, dtype=torch.bfloat16) * 0.05)(B, Sq, M)), 'c_kv': _w((lambda *s: torch.randn(*s, dtype=torch.bfloat16) * 1.6)(B, Sk, Dc)), 'w_q': _w((lambda *s: torch.randn(*s, dtype=torch.bfloat16) * 0.8)(M, H, D) * M ** (-0.5)), 'w_uk': _w((lambda *s: torch.randn(*s, dtype=torch.bfloat16) * 0.8)(Dc, H, D) * Dc ** (-0.5)), 'w_uv': _w((lambda *s: torch.randn(*s, dtype=torch.bfloat16) * 1.6)(Dc, H, D) * Dc ** (-0.5)), 'w_o': _w((lambda *s: torch.randn(*s, dtype=torch.bfloat16) * 1.6)(H, D, M) * (H * D) ** (-0.5))}
    _A_in = _A_setup()

    def _B_setup():
        B, S, D, F = (4, 1, 576, 4608)
        return {'x': _w((lambda *s: torch.randn(*s, dtype=torch.bfloat16) * 0.05)(B, S, D)), 'w_gate': _w((lambda *s: torch.randn(*s, dtype=torch.bfloat16) * 0.05)(D, F)), 'w_up': _w((lambda *s: torch.randn(*s, dtype=torch.bfloat16) * 0.05)(D, F)), 'w_down': _w((lambda *s: torch.randn(*s, dtype=torch.bfloat16) * 0.05)(F, D))}
    _B_in = _B_setup()
    return {'A_x': _A_in['x'], 'A_c_kv': _A_in['c_kv'], 'A_w_q': _A_in['w_q'], 'A_w_uk': _A_in['w_uk'], 'A_w_uv': _A_in['w_uv'], 'A_w_o': _A_in['w_o'], 'B_x': _B_in['x'], 'B_w_gate': _B_in['w_gate'], 'B_w_up': _B_in['w_up'], 'B_w_down': _B_in['w_down'], 'c': _w((lambda *s: torch.randn(*s, dtype=torch.bfloat16) * 0.1)(4, 576) * 8.0), 'w_mod': _w((lambda *s: torch.randn(*s, dtype=torch.bfloat16) * 0.1)(576, 6 * 576) * 576 ** (-0.5) * 8.0)}

def reference(A_x, A_c_kv, A_w_q, A_w_uk, A_w_uv, A_w_o, B_x, B_w_gate, B_w_up, B_w_down, c, w_mod):

    def _A_ref(x, c_kv, w_q, w_uk, w_uv, w_o):
        B, Sq, M = (x.shape[0], x.shape[1], x.shape[2])
        Sk = c_kv.shape[1]
        H, D = (w_q.shape[1], w_q.shape[2])
        q = torch.einsum('bqm,mhd->bhqd', x, w_q)
        k = torch.einsum('bkc,chd->bhkd', c_kv, w_uk)
        v = torch.einsum('bkc,chd->bhkd', c_kv, w_uv)
        scores = torch.einsum('bhqd,bhkd->bhqk', q, k) * D ** (-0.5)
        off = Sk - Sq
        qi = torch.arange(Sq)[:, None]
        kj = torch.arange(Sk)[None, :]
        cmask = kj <= qi + off
        scores = torch.where(cmask[None, None], scores, -1000000000.0)
        p = _softmax(scores, axis=-1)
        ctx = torch.einsum('bhqk,bhkd->bhqd', p, v)
        return torch.einsum('bhqd,hdm->bqm', ctx, w_o)

    def _B_ref(x, w_gate, w_up, w_down):
        g = _silu(x @ w_gate)
        u = x @ w_up
        return g * u @ w_down
    x = A_x
    mod = (_silu(c) @ w_mod).reshape(c.shape[0], 6, 1, -1)
    sa, ca, ga, sb, cb, gb = (mod[:, 0].clone(), mod[:, 1].clone(), mod[:, 2].clone(), mod[:, 3].clone(), mod[:, 4].clone(), mod[:, 5].clone())
    h = _layernorm(x, axis=-1) * (1 + ca) + sa
    x = x + ga * _A_ref(h, A_c_kv, A_w_q, A_w_uk, A_w_uv, A_w_o)
    h = _layernorm(x, axis=-1) * (1 + cb) + sb
    x = x + gb * _B_ref(h, B_w_gate, B_w_up, B_w_down)
    return x
```

```cpp
#include <cuda_runtime.h>
#include <cuda_bf16.h>
#include <cuda.h>
#include <stdint.h>

typedef __nv_bfloat16 bf16;

#define TUNABLES \
  TV(W_A, 36) TV(W_P, 48) TV(W_B, 32) TV(W_G, 30) TV(PACE_A, 44000) TV(PACE_PS, 45000) TV(PACE_B, 45000) TV(PACE_G, 40000) TV(ORDER, 0) \
  TV(PACE_T0, 300) TV(STAG, 350) \
  TV(MOD2_DELAY, 7500) TV(MOD2_STEP, 200) TV(T_E1, 1400) TV(D_E2, 0) TV(D_E3, 0) TV(D_E4, 0) TV(D_E5, 0) TV(D_E6, 0) TV(D_E7, 0) TV(D_E7B, 0) TV(D_E8, 0) \
  TV(TH1, 64) TV(TH2, 64) TV(TH3, 64) TV(TH4, 32) TV(TH5, 64) TV(TH6, 8) TV(TH7, 0) TV(TH8, 64) TV(T_CLR, 1000) TV(D_CLR, 0) TV(T_GATH, 6000) TV(NUMA, 1) TV(NEAR_MAX, 430) TV(PROBE_MAX, 6)
#define TV(n, d) constexpr int C_##n = d;
TUNABLES
#undef TV
#define TN(n) (C_##n)
#define SPIN_LIMIT 1000000
#define WAIT_UNTIL(ns) do { while ((int)(gtime32() - t0) < (ns)) ; } while (0)
#define DELAY(n) do { const int n_ = (n); if (n_ > 0) { unsigned c0_ = clock(); while ((int)((unsigned)clock() - c0_) < n_) ; } } while (0)

constexpr int X_OFF   = 0;
constexpr int WO_OFF  = X_OFF;
constexpr int GA_OFF  = X_OFF + 36864;
constexpr int M1_OFF  = X_OFF + 98304;
constexpr int Y1_OFF  = 131072;
constexpr int SC_OFF  = Y1_OFF;
constexpr int Y2_OFF  = Y1_OFF + 36864;
constexpr int Y3_OFF  = Y2_OFF + 32768;
constexpr int DN_OFF  = Y2_OFF;
constexpr int ACT_OFF = Y3_OFF + 16384;
constexpr int ACT_P   = 1168;
constexpr int AC2_OFF = ACT_OFF + 4 * ACT_P;
constexpr int AC2_P   = 304;
constexpr int RED_OFF = AC2_OFF + 8 * AC2_P;
constexpr int SMX_OFF = RED_OFF + 4096;
constexpr int ST_OFF  = SMX_OFF + 1024;
constexpr int BAR_OFF = ST_OFF + 768;
constexpr int TAB_OFF = BAR_OFF + 640;
constexpr int SMEM_BYTES = TAB_OFF + 46 * 32;
static_assert(SMEM_BYTES <= 232448, "smem");
static_assert(ACT_OFF % 16 == 0 && AC2_OFF % 16 == 0 && RED_OFF % 16 == 0 && BAR_OFF % 8 == 0, "align");

constexpr int B_WQ = 0, B_WUK = 4, B_CKV = 8, B_WUV = 24, B_WO = 28, B_GU = 31, B_DN = 43;
constexpr int B_SRECV = 56, B_GA = 60, B_GB = 61, B_DONE = 62;
constexpr int B_PRDY = 64, B_TFREE = 68, B_QDONE = 72, B_ADONE = 73, B_LRDY = 74, B_MASK = 75, B_SC = 76, B_UVF = 77;
constexpr unsigned long long LOG2_COUNTS = 0x0031144444442222ull;
constexpr int B_EMPTY = 80;
constexpr int NFFN = 116;
constexpr int NSTEP = 46;

constexpr int U_PROBE = 0;
constexpr int U_MOD1  = 2;
constexpr int U_X2    = 10;
constexpr int U_Q     = 16;
constexpr int U_QA    = 80;
constexpr int MOD2_G  = 112 * 8192;
constexpr int EPOCH_G = MOD2_G + 40960;
constexpr int BLK_G   = 2 * 1024 * 1024;
constexpr size_t BOX_BYTES = (size_t)BLK_G + 128 * 65536;
__device__ __align__(256) char g_box[BOX_BYTES + 2 * 1024 * 1024];
__device__ __forceinline__ int orient(int u) { return __popc(u & 0x59) & 1; }
#define NTHR 608
#define WS(k, cond)
#define WV(k, v)
#define TS(k)
#define TSW(k, t)
#define FA(k)
#define FB(k)

struct Prm { const bf16* x; const bf16* c; const bf16* wmod; bf16* out; char* box;
};
struct Maps { CUtensorMap wq, wuk, ckv, wuv, wo, gate, up, down, mod2; };
struct Sched { uint2 e[64]; };

__device__ __forceinline__ uint32_t smem_u32(const void* p) { return (uint32_t)__cvta_generic_to_shared(p); }
__device__ __forceinline__ long long gtime64() { long long t; asm volatile("mov.u64 %0, %%globaltimer;" : "=l"(t)); return t; }
__device__ __forceinline__ unsigned gtime32() { unsigned t; asm volatile("mov.u32 %0, %%globaltimer_lo;" : "=r"(t)); return t; }
__device__ __forceinline__ void mbar_init(uint32_t bar, int cnt) { asm volatile("mbarrier.init.shared::cta.b64 [%0], %1;" :: "r"(bar), "r"(cnt) : "memory"); }
__device__ __forceinline__ void mbar_expect_tx(uint32_t bar, uint32_t bytes) { asm volatile("mbarrier.arrive.expect_tx.shared::cta.b64 _, [%0], %1;" :: "r"(bar), "r"(bytes) : "memory"); }
__device__ __forceinline__ void mbar_arrive(uint32_t bar) { asm volatile("mbarrier.arrive.shared::cta.b64 _, [%0];" :: "r"(bar) : "memory"); }
__device__ __forceinline__ bool mbar_try(uint32_t bar, uint32_t parity) {
  uint32_t ok;
  asm volatile("{\n.reg .pred p;\nmbarrier.try_wait.parity.shared::cta.b64 p, [%1], %2;\nselp.u32 %0, 1, 0, p;\n}" : "=r"(ok) : "r"(bar), "r"(parity) : "memory");
  return ok;
}
__device__ __forceinline__ bool mbar_test(uint32_t bar, uint32_t parity) {
  uint32_t ok;
  asm volatile("{\n.reg .pred p;\nmbarrier.test_wait.parity.shared::cta.b64 p, [%1], %2;\nselp.u32 %0, 1, 0, p;\n}" : "=r"(ok) : "r"(bar), "r"(parity) : "memory");
  return ok;
}
__device__ __forceinline__ void mbar_wait(uint32_t bar, uint32_t parity) {
  asm volatile("{\n.reg .pred p, q;\n.reg .u32 n;\nmov.u32 n, 0;\n"
               "W_%=:\nmbarrier.try_wait.parity.shared::cta.b64 p, [%0], %1;\n@p bra D_%=;\n"
               "add.u32 n, n, 1;\nsetp.lt.u32 q, n, %2;\n@q bra W_%=;\nD_%=:\n}"
               :: "r"(bar), "r"(parity), "n"(SPIN_LIMIT) : "memory");
}
__device__ __forceinline__ void mbar_wait2(uint32_t b0, uint32_t b1) {
  asm volatile("{\n.reg .pred p0, p1, q;\n.reg .u32 n;\nmov.u32 n, 0;\n"
               "W_%=:\n"
               "mbarrier.try_wait.parity.shared::cta.b64 p1, [%1], 0;\n"
               "mbarrier.try_wait.parity.shared::cta.b64 p0, [%0], 0;\n"
               "and.pred p0, p0, p1;\n@p0 bra D_%=;\n"
               "add.u32 n, n, 1;\nsetp.lt.u32 q, n, %2;\n@q bra W_%=;\nD_%=:\n}"
               :: "r"(b0), "r"(b1), "n"(SPIN_LIMIT) : "memory");
}
__device__ __forceinline__ void mbar_wait4(uint32_t b0, uint32_t b1, uint32_t b2, uint32_t b3) {
  asm volatile("{\n.reg .pred p0, p1, p2, p3, q;\n.reg .u32 n;\nmov.u32 n, 0;\n"
               "W_%=:\n"
               "mbarrier.try_wait.parity.shared::cta.b64 p3, [%3], 0;\n"
               "mbarrier.try_wait.parity.shared::cta.b64 p2, [%2], 0;\n"
               "mbarrier.try_wait.parity.shared::cta.b64 p1, [%1], 0;\n"
               "mbarrier.try_wait.parity.shared::cta.b64 p0, [%0], 0;\n"
               "and.pred p0, p0, p1;\nand.pred p2, p2, p3;\nand.pred p0, p0, p2;\n@p0 bra D_%=;\n"
               "add.u32 n, n, 1;\nsetp.lt.u32 q, n, %4;\n@q bra W_%=;\nD_%=:\n}"
               :: "r"(b0), "r"(b1), "r"(b2), "r"(b3), "n"(SPIN_LIMIT) : "memory");
}
__device__ __forceinline__ bool mbar_test4(uint32_t b0, uint32_t b1, uint32_t b2, uint32_t b3) {
  uint32_t ok;
  asm volatile("{\n.reg .pred p0, p1, p2, p3;\n"
               "mbarrier.test_wait.parity.shared::cta.b64 p3, [%4], 0;\n"
               "mbarrier.test_wait.parity.shared::cta.b64 p2, [%3], 0;\n"
               "mbarrier.test_wait.parity.shared::cta.b64 p1, [%2], 0;\n"
               "mbarrier.test_wait.parity.shared::cta.b64 p0, [%1], 0;\n"
               "and.pred p0, p0, p1;\nand.pred p2, p2, p3;\nand.pred p0, p0, p2;\nselp.u32 %0, 1, 0, p0;\n}"
               : "=r"(ok) : "r"(b0), "r"(b1), "r"(b2), "r"(b3) : "memory");
  return ok;
}
__device__ __forceinline__ void tma3d(uint32_t dst, const CUtensorMap* m, int c0, int c1, int c2, uint32_t bar, uint64_t pol) {
  asm volatile("cp.async.bulk.tensor.3d.shared::cluster.global.mbarrier::complete_tx::bytes.L2::cache_hint [%0], [%1, {%3, %4, %5}], [%2], %6;"
               :: "r"(dst), "l"(m), "r"(bar), "r"(c0), "r"(c1), "r"(c2), "l"(pol) : "memory");
}
__device__ __forceinline__ void bar_sync(int id, int n) { asm volatile("bar.sync %0, %1;" :: "r"(id), "r"(n) : "memory"); }
__device__ __forceinline__ void fence_async() { asm volatile("fence.proxy.async.shared::cta;" ::: "memory"); }
__device__ __forceinline__ uint4 ldg_rlx(const void* p) {
  unsigned long long a, b;
  asm volatile("ld.relaxed.gpu.global.v2.b64 {%0,%1}, [%2];" : "=l"(a), "=l"(b) : "l"(p) : "memory");
  return make_uint4((unsigned)a, (unsigned)(a >> 32), (unsigned)b, (unsigned)(b >> 32));
}
__device__ __forceinline__ uint2 ldg_rlx64(const void* p) {
  unsigned long long a;
  asm volatile("ld.relaxed.gpu.global.b64 %0, [%1];" : "=l"(a) : "l"(p) : "memory");
  return make_uint2((unsigned)a, (unsigned)(a >> 32));
}
__device__ __forceinline__ unsigned ldg_rlx32(const void* p) { unsigned v; asm volatile("ld.relaxed.gpu.global.u32 %0, [%1];" : "=r"(v) : "l"(p) : "memory"); return v; }
__device__ __forceinline__ void stg_rlx(void* p, uint4 v) {
  unsigned long long a = ((unsigned long long)v.y << 32) | v.x, b = ((unsigned long long)v.w << 32) | v.z;
  asm volatile("st.relaxed.gpu.global.v2.b64 [%0], {%1,%2};" :: "l"(p), "l"(a), "l"(b) : "memory");
}
__device__ __forceinline__ void stg_rlx64(void* p, unsigned x, unsigned y) {
  unsigned long long a = ((unsigned long long)y << 32) | x;
  asm volatile("st.relaxed.gpu.global.b64 [%0], %1;" :: "l"(p), "l"(a) : "memory");
}
__device__ __forceinline__ void stg_rlx64_if(bool c, void* p, unsigned x, unsigned y) {
  unsigned long long a = ((unsigned long long)y << 32) | x;
  asm volatile("{\n.reg .pred p;\nsetp.ne.u32 p, %2, 0;\n@p st.relaxed.gpu.global.b64 [%0], %1;\n}" :: "l"(p), "l"(a), "r"((unsigned)c) : "memory");
}
__device__ __forceinline__ void ldg_rlx_if(bool c, const void* p, uint4& v) {
  unsigned long long a = ((unsigned long long)v.y << 32) | v.x, b = ((unsigned long long)v.w << 32) | v.z;
  asm volatile("{\n.reg .pred p;\nsetp.ne.u32 p, %3, 0;\n@p ld.relaxed.gpu.global.v2.b64 {%0,%1}, [%2];\n}" : "+l"(a), "+l"(b) : "l"(p), "r"((unsigned)c) : "memory");
  v = make_uint4((unsigned)a, (unsigned)(a >> 32), (unsigned)b, (unsigned)(b >> 32));
}
__device__ __forceinline__ void stg_rlx32(void* p, unsigned x) { asm volatile("st.relaxed.gpu.global.u32 [%0], %1;" :: "l"(p), "r"(x) : "memory"); }
__device__ __forceinline__ uint32_t lds32(uint32_t a) { uint32_t v; asm volatile("ld.shared.u32 %0, [%1];" : "=r"(v) : "r"(a) : "memory"); return v; }
__device__ __forceinline__ float lds32f(uint32_t a) { float v; asm volatile("ld.shared.f32 %0, [%1];" : "=f"(v) : "r"(a) : "memory"); return v; }
__device__ __forceinline__ uint2 lds64(uint32_t a) { uint2 v; asm volatile("ld.shared.v2.u32 {%0,%1}, [%2];" : "=r"(v.x), "=r"(v.y) : "r"(a) : "memory"); return v; }
__device__ __forceinline__ uint4 lds128(uint32_t a) { uint4 v; asm volatile("ld.shared.v4.u32 {%0,%1,%2,%3}, [%4];" : "=r"(v.x), "=r"(v.y), "=r"(v.z), "=r"(v.w) : "r"(a) : "memory"); return v; }
__device__ __forceinline__ void sts16(uint32_t a, uint16_t v) { asm volatile("st.shared.u16 [%0], %1;" :: "r"(a), "h"(v) : "memory"); }
__device__ __forceinline__ void sts32(uint32_t a, uint32_t v) { asm volatile("st.shared.u32 [%0], %1;" :: "r"(a), "r"(v) : "memory"); }
__device__ __forceinline__ void sts32f(uint32_t a, float v) { asm volatile("st.shared.f32 [%0], %1;" :: "r"(a), "f"(v) : "memory"); }
__device__ __forceinline__ void sts64f(uint32_t a, float x, float y) { asm volatile("st.shared.v2.f32 [%0], {%1,%2};" :: "r"(a), "f"(x), "f"(y) : "memory"); }
__device__ __forceinline__ void sts128(uint32_t a, uint4 v) { asm volatile("st.shared.v4.u32 [%0], {%1,%2,%3,%4};" :: "r"(a), "r"(v.x), "r"(v.y), "r"(v.z), "r"(v.w) : "memory"); }
__device__ __forceinline__ void ldsm4t(uint32_t (&r)[4], uint32_t a) {
  asm volatile("ldmatrix.sync.aligned.m8n8.x4.trans.shared.b16 {%0,%1,%2,%3}, [%4];" : "=r"(r[0]), "=r"(r[1]), "=r"(r[2]), "=r"(r[3]) : "r"(a) : "memory");
}
__device__ __forceinline__ void ldsm4(uint32_t (&r)[4], uint32_t a) {
  asm volatile("ldmatrix.sync.aligned.m8n8.x4.shared.b16 {%0,%1,%2,%3}, [%4];" : "=r"(r[0]), "=r"(r[1]), "=r"(r[2]), "=r"(r[3]) : "r"(a) : "memory");
}
__device__ __forceinline__ void ldsm2t(uint32_t (&r)[2], uint32_t a) {
  asm volatile("ldmatrix.sync.aligned.m8n8.x2.trans.shared.b16 {%0,%1}, [%2];" : "=r"(r[0]), "=r"(r[1]) : "r"(a) : "memory");
}
__device__ __forceinline__ void mma16(float (&d)[4], const uint32_t (&a)[4], uint32_t b0, uint32_t b1) {
  asm volatile("mma.sync.aligned.m16n8k16.row.col.f32.bf16.bf16.f32 {%0,%1,%2,%3}, {%4,%5,%6,%7}, {%8,%9}, {%0,%1,%2,%3};"
               : "+f"(d[0]), "+f"(d[1]), "+f"(d[2]), "+f"(d[3]) : "r"(a[0]), "r"(a[1]), "r"(a[2]), "r"(a[3]), "r"(b0), "r"(b1));
}
__device__ __forceinline__ void mma8(float (&d)[4], const uint32_t (&a)[2], uint32_t b0) {
  asm volatile("mma.sync.aligned.m16n8k8.row.col.f32.bf16.bf16.f32 {%0,%1,%2,%3}, {%4,%5}, {%6}, {%0,%1,%2,%3};"
               : "+f"(d[0]), "+f"(d[1]), "+f"(d[2]), "+f"(d[3]) : "r"(a[0]), "r"(a[1]), "r"(b0));
}
__device__ __forceinline__ uint32_t pack_bf16(float lo, float hi) { uint32_t r; asm("cvt.rn.bf16x2.f32 %0, %1, %2;" : "=r"(r) : "f"(hi), "f"(lo)); return r; }
__device__ __forceinline__ uint16_t to_bf16(float v) { return (uint16_t)(pack_bf16(v, 0.f) & 0xFFFFu); }
__device__ __forceinline__ float bf_lo(uint32_t v) { return __uint_as_float(v << 16); }
__device__ __forceinline__ float bf_hi(uint32_t v) { return __uint_as_float(v & 0xFFFF0000u); }
__device__ __forceinline__ float ex2(float x) { float r; asm("ex2.approx.ftz.f32 %0, %1;" : "=f"(r) : "f"(x)); return r; }
__device__ __forceinline__ float silu(float v) { return __fdividef(v, 1.f + __expf(-v)); }
__device__ __forceinline__ unsigned tagf(float v, unsigned par) { return (__float_as_uint(v) & ~1u) | par; }
__device__ __forceinline__ unsigned tagb(unsigned w, unsigned par) { return ((w + ((w >> 1) & 1u)) & ~1u) | par; }
__device__ __forceinline__ bool ok4(const uint4& v, unsigned par) { return ((((v.x ^ par) | (v.y ^ par) | (v.z ^ par) | (v.w ^ par)) & 1u) == 0); }
__device__ __forceinline__ bool ok2(const uint4& v, unsigned par) { return ((((v.x ^ par) | (v.z ^ par)) & 1u) == 0); }
__device__ __forceinline__ int fkey(float f) { int b = __float_as_int(f); return b ^ ((b >> 31) & 0x7FFFFFFF); }
__device__ __forceinline__ float funkey(int k) { return __int_as_float(k ^ ((k >> 31) & 0x7FFFFFFF)); }

template <int TA, int TB>
__device__ __forceinline__ void wgmma_n32(float (&d)[16], uint64_t da, uint64_t db, int accum) {
  asm volatile("{\n.reg .pred p;\nsetp.ne.b32 p, %18, 0;\n"
               "wgmma.mma_async.sync.aligned.m64n32k16.f32.bf16.bf16 {%0,%1,%2,%3,%4,%5,%6,%7,%8,%9,%10,%11,%12,%13,%14,%15}, %16, %17, p, 1, 1, %19, %20;\n}"
               : "+f"(d[0]), "+f"(d[1]), "+f"(d[2]), "+f"(d[3]), "+f"(d[4]), "+f"(d[5]), "+f"(d[6]), "+f"(d[7]),
                 "+f"(d[8]), "+f"(d[9]), "+f"(d[10]), "+f"(d[11]), "+f"(d[12]), "+f"(d[13]), "+f"(d[14]), "+f"(d[15])
               : "l"(da), "l"(db), "r"(accum), "n"(TA), "n"(TB) : "memory");
}
__device__ __forceinline__ void wg_fence() { asm volatile("wgmma.fence.sync.aligned;" ::: "memory"); }
__device__ __forceinline__ void wg_commit() { asm volatile("wgmma.commit_group.sync.aligned;" ::: "memory"); }
__device__ __forceinline__ void wg_wait0() { asm volatile("wgmma.wait_group.sync.aligned 0;" ::: "memory"); }
__device__ __forceinline__ uint64_t mkdesc(uint32_t addr, uint32_t sbo, uint32_t swz) {
  return (uint64_t)((addr & 0x3FFFF) >> 4) | ((uint64_t)1 << 16) | ((uint64_t)(sbo >> 4) << 32) | ((uint64_t)swz << 62);
}

__device__ __forceinline__ void poll_one(const void* p, int src, unsigned par) {
  const void* lp = (const void*)__shfl_sync(0xffffffffu, (unsigned long long)p, src);
#pragma unroll 1
  for (int it = 0; it < SPIN_LIMIT; it++) if (((ldg_rlx32(lp) ^ par) & 1u) == 0) break;
}
template <bool ALL4>
__device__ __forceinline__ void poll_fin(const void* p, unsigned par, uint4& v, int th) {
#pragma unroll 1
  for (int it = 0; it < SPIN_LIMIT; it++) {
    const bool bad = !(ALL4 ? ok4(v, par) : ok2(v, par));
    const unsigned m = __ballot_sync(0xffffffffu, bad);
    if (!m) break;
    if (__popc(m) > th) poll_one(p, __ffs(m) - 1, par);
    ldg_rlx_if(bad, p, v);
  }
}
template <bool ALL4>
__device__ __forceinline__ void poll_fin2(const void* p0, const void* p1, unsigned par, uint4& v0, uint4& v1, int th) {
#pragma unroll 1
  for (int it = 0; it < SPIN_LIMIT; it++) {
    const bool b0 = !(ALL4 ? ok4(v0, par) : ok2(v0, par)), b1 = !(ALL4 ? ok4(v1, par) : ok2(v1, par));
    const unsigned m0 = __ballot_sync(0xffffffffu, b0), m1 = __ballot_sync(0xffffffffu, b1);
    if (!(m0 | m1)) break;
    if (__popc(m0) + __popc(m1) > th) poll_one(m0 ? p0 : p1, __ffs(m0 ? m0 : m1) - 1, par);
    ldg_rlx_if(b0, p0, v0);
    ldg_rlx_if(b1, p1, v1);
  }
}
template <bool ALL4>
__device__ __forceinline__ uint4 poll16(const void* p, unsigned par, int th) { uint4 v = make_uint4(par ^ 1u, 0, 0, 0); poll_fin<ALL4>(p, par, v, th); return v; }
template <bool ALL4>
__device__ __forceinline__ void poll16x2(const void* p0, const void* p1, unsigned par, uint4& v0, uint4& v1, int th) {
  v0 = make_uint4(par ^ 1u, 0, 0, 0); v1 = v0; poll_fin2<ALL4>(p0, p1, par, v0, v1, th);
}
__device__ __forceinline__ void poll32_fin(const void* p, unsigned par, unsigned& v) {
#pragma unroll 1
  for (int it = 0; it < SPIN_LIMIT; it++) {
    const bool bad = (v ^ par) & 1u;
    if (!__any_sync(0xffffffffu, bad)) break;
    DELAY(300);
    if (bad) v = ldg_rlx32(p);
  }
}
#define KEEP(x) asm volatile("" : "+r"(x))
#define KEEPL(x) asm volatile("" : "+l"(x))

template <int B1, int B0>
__device__ __forceinline__ float xreduce4(float s0, float s1, float s2, float s3, int lane) {
  const bool hi = lane & B1, lo = lane & B0;
  float a = hi ? s0 : s2, b = hi ? s1 : s3;
  a = __shfl_xor_sync(0xffffffffu, a, B1); b = __shfl_xor_sync(0xffffffffu, b, B1);
  s0 = (hi ? s2 : s0) + a; s1 = (hi ? s3 : s1) + b;
  float c = lo ? s0 : s1;
  c = __shfl_xor_sync(0xffffffffu, c, B0);
  return (lo ? s1 : s0) + c;
}
template <bool MAX>
__device__ __forceinline__ float xreduce8(const float (&a)[8], int lane) {
  const bool b4 = lane & 16, b3 = lane & 8, b2 = lane & 4;
  float u[4], w[2];
#pragma unroll
  for (int e = 0; e < 4; e++) { float snd = b4 ? a[e] : a[4 + e], keep = b4 ? a[4 + e] : a[e]; snd = __shfl_xor_sync(0xffffffffu, snd, 16); u[e] = MAX ? fmaxf(keep, snd) : keep + snd; }
#pragma unroll
  for (int e = 0; e < 2; e++) { float snd = b3 ? u[e] : u[2 + e], keep = b3 ? u[2 + e] : u[e]; snd = __shfl_xor_sync(0xffffffffu, snd, 8); w[e] = MAX ? fmaxf(keep, snd) : keep + snd; }
  float snd = b2 ? w[0] : w[1], keep = b2 ? w[1] : w[0];
  snd = __shfl_xor_sync(0xffffffffu, snd, 4);
  return MAX ? fmaxf(keep, snd) : keep + snd;
}
#define UF(x) __uint_as_float(x)

__device__ __forceinline__ float reduce_pieces(const char* src, int n, unsigned tag, uint32_t sb, int warp, int lane, int bk) {
  const int g = lane >> 2, t = lane & 3;
  uint32_t sa = sb + RED_OFF + (warp * 32 + t * 8 + g) * 4;
  KEEP(sa);
  uint4 v = make_uint4(warp * 8 + g < n ? tag ^ 1u : tag, 0, tag, 0);
  poll_fin<false>(src, tag, v, bk);
  v.x &= ~1u; v.z &= ~1u;
  const float a[8] = {bf_lo(v.x), bf_hi(v.x), bf_lo(v.y), bf_hi(v.y), bf_lo(v.z), bf_hi(v.z), bf_lo(v.w), bf_hi(v.w)};
  sts32f(sa, xreduce8<false>(a, lane));
  float r = 0.f;
  if (warp == 0) {
    bar_sync(3, 512);
    float w[16];
#pragma unroll
    for (int q = 0; q < 16; q++) w[q] = lds32f(sb + RED_OFF + (q * 32 + lane) * 4);
#pragma unroll
    for (int q = 0; q < 8; q++) w[q] += w[q + 8];
    r = ((w[0] + w[4]) + (w[1] + w[5])) + ((w[2] + w[6]) + (w[3] + w[7]));
  } else {
    asm volatile("bar.arrive 3, 512;" ::: "memory");
  }
  return r;
}
__device__ __forceinline__ void send_pieces(char* G, const uint32_t (&off)[3], const float (&d)[3][4], int t, unsigned tag) {
  uint32_t w0[3], w1[3], o[3];
#pragma unroll
  for (int m = 0; m < 3; m++) {
    w0[m] = pack_bf16(d[m][0], d[m][1]); w1[m] = pack_bf16(d[m][2], d[m][3]);
    o[m] = __shfl_xor_sync(0xffffffffu, (t & 1) ? w0[m] : w1[m], 1);
  }
#pragma unroll
  for (int m = 0; m < 3; m++) stg_rlx64_if(t < 2, G + off[m], tagb((t & 1) ? o[m] : w0[m], tag), (t & 1) ? w1[m] : o[m]);
}
__device__ __forceinline__ uint32_t hsel(uint32_t sb, int c) { return (lds32(sb + ST_OFF + 80 + (c >> 5) * 4) >> (c & 31)) & 1u; }

__global__ void __cluster_dims__(2, 1, 1) __launch_bounds__(NTHR, 1)
fused_kernel(const __grid_constant__ Prm A, const __grid_constant__ Maps M, const __grid_constant__ Sched S) {
  extern __shared__ __align__(1024) char sm[];
  const int tid = __shfl_sync(0xffffffffu, (int)threadIdx.x, threadIdx.x & 31), cta = __shfl_sync(0xffffffffu, (int)blockIdx.x, 0);
  const int warp = __shfl_sync(0xffffffffu, tid >> 5, 0), lane = tid & 31, g = lane >> 2, t = lane & 3;
  const uint32_t sb = __shfl_sync(0xffffffffu, smem_u32(sm), 0);
  const uint32_t bars = sb + BAR_OFF;
  const unsigned t0 = gtime32();
  TS(0);

  uint2 se0 = make_uint2(0, 0), se1 = se0;
  if (warp == 16) { se0 = __ldg(&S.e[lane]); se1 = __ldg(&S.e[32 + lane]); }
  unsigned par = 0;
  uint4 cx = make_uint4(0, 0, 0, 0);
  uint4 xx = make_uint4(0, 0, 0, 0);
  if (warp < 16) {
    if (cta < 72 && warp < 12) {
      const char* wm = (const char*)A.wmod + cta * 32 + (lane & 1) * 16;
#pragma unroll
      for (int q = 0; q < 3; q++) {
        const int k = warp * 48 + q * 16 + (lane >> 1);
        asm volatile("cp.async.cg.shared.global [%0], [%1], 16;" :: "r"(sb + M1_OFF + (lane & 1) * 9216 + k * 16), "l"(wm + (size_t)k * 6912) : "memory");
      }
    }
    if (tid < 288) {
      if (cta < 72 || cta >= 128) cx = __ldg((const uint4*)A.c + tid);
      xx = __ldg((const uint4*)A.x + tid);
    }
    par = ldg_rlx32(A.box + EPOCH_G + (tid - (int)threadIdx.x));
    if (lane == 0) {
#pragma unroll
      for (int k = 0; k < 4; k++) mbar_init(bars + 8 * (warp + 16 * k), 1);
      mbar_init(bars + 8 * (warp + 64), 1 << ((int)(LOG2_COUNTS >> (4 * warp)) & 15));
      if ((warp >> 2) == 2) mbar_expect_tx(bars + 8 * (warp + 48), 8192);
      asm volatile("fence.mbarrier_init.release.cluster;" ::: "memory");
    }
    __syncwarp();
    if (tid < 128) sts32(sb + SMX_OFF + tid * 4, 0x80000000u);
  }
  if (warp == 17 || warp == 18) {
    const int hf = warp - 17;
    char* p0a = A.box + U_PROBE * 8192 + (cta & 127) * 32 + hf * 4096;
    char* p1a = A.box + BLK_G + (cta & 127) * 65536 + hf * 4096;
    if (lane < 4 && cta < 128) stg_rlx((lane < 2 ? p0a : p1a) + (lane & 1) * 16, make_uint4(0, 0, 0, 0));
    if (lane == 0) sts32(sb + ST_OFF + 64 + hf * 4, 0);
    bar_sync(8, 64);
    asm volatile("bar.arrive 0, %0;" :: "n"(NTHR) : "memory");
    if (lane == 0 && cta < 128) {
#pragma unroll 1
      for (int k = 0; k < 2; k++) {
        unsigned best = 0xffffffffu;
#pragma unroll 1
        for (int r = 0; r < TN(PROBE_MAX); r++) {
          unsigned v;
          const unsigned cs = clock();
          asm volatile("atom.relaxed.gpu.global.exch.b32 %0, [%1], 0;" : "=r"(v) : "l"(k ? p1a : p0a) : "memory");
          if (v == 0) best = min(best, (unsigned)clock() - cs);
          if (best < (unsigned)TN(NEAR_MAX)) sts32(sb + ST_OFF + 64 + k * 4, 2u | hf);
          if (lds32(sb + ST_OFF + 64 + k * 4)) break;
        }
        sts32(sb + ST_OFF + 72 + hf * 4, best);
      }
    }
    __syncwarp();
    bar_sync(10, 96);
  } else {
    bar_sync(0, NTHR);
    if (warp == 16) asm volatile("bar.arrive 10, 96;" ::: "memory");
  }

  if (warp > 16) {
    if (cta >= 128) return;
    asm volatile("barrier.cluster.arrive.relaxed.aligned;" ::: "memory");
    char* const G = A.box;
    const int hf = warp - 17, ht = tid - 544;
    char* const blk = G + BLK_G + cta * 65536;
    const unsigned epoch = ldg_rlx32(G + EPOCH_G + (tid - (int)threadIdx.x)) + 1u;
    bar_sync(8, 64);
    unsigned hb = lds32(sb + ST_OFF + 68);
    { const uint2 lt = lds64(sb + ST_OFF + 72); hb = TN(NUMA) ? (hb ? hb & 1u : (lt.x > lt.y ? 1u : 0u)) : 0u; }
    TSW(25, 544);
    WAIT_UNTIL(TN(T_CLR));
#pragma unroll 1
    for (int u = 0; u < 7; u++) {
      if (cta >= 72 && (u == 1 || u == 3)) continue;
      char* pa = blk + u * 8192 + ((hb ^ (u & 1)) << 12) + ht * 16;
#pragma unroll
      for (int q = 0; q < 4; q++) stg_rlx(pa + q * 1024, make_uint4(0, 0, 0, 0));
      DELAY(TN(D_CLR));
    }
    TSW(26, 544);
    bar_sync(8, 64);
    if (ht == 0) { __threadfence(); stg_rlx32(blk + 7 * 8192, (epoch << 1) | hb); }
    TSW(27, 544);
    WAIT_UNTIL(TN(T_GATH));
    {
      const char* pa = G + BLK_G + ht * 65536 + 7 * 8192;
      const unsigned want = epoch & 0x7fffffffu;
      unsigned v0 = ldg_rlx32(pa), v1 = ldg_rlx32(pa + 64 * 65536);
#pragma unroll 1
      for (int it = 0; it < SPIN_LIMIT; it++) {
        const bool b0 = (v0 >> 1) != want, b1 = (v1 >> 1) != want;
        if (!__any_sync(0xffffffffu, b0 || b1)) break;
        DELAY(200);
        if (b0) v0 = ldg_rlx32(pa);
        if (b1) v1 = ldg_rlx32(pa + 64 * 65536);
      }
      const unsigned m0 = __ballot_sync(0xffffffffu, v0 & 1u), m1 = __ballot_sync(0xffffffffu, v1 & 1u);
      if (lane == 0) { sts32(sb + ST_OFF + 80 + hf * 4, m0); sts32(sb + ST_OFF + 88 + hf * 4, m1); }
    }
    if (lane == 0) mbar_arrive(bars + 8 * B_MASK);
    TSW(28, 544);
    bar_sync(8, 64);
    if (hf == 1) {
      const int c0 = lane * 4 + (cta & 1) * 2;
      char* m0 = G + BLK_G + c0 * 65536 + 5 * 8192 + ((hsel(sb, c0) ^ 1u) << 12) + 2048 + (cta >> 1) * 32;
      char* m1 = G + BLK_G + (c0 + 1) * 65536 + 5 * 8192 + ((hsel(sb, c0 + 1) ^ 1u) << 12) + 2048 + (cta >> 1) * 32;
      mbar_wait(bars + 8 * B_LRDY, 0);
      float lp[16];
#pragma unroll
      for (int q = 0; q < 16; q++) lp[q] = lds32f(sb + RED_OFF + (q * 32 + lane) * 4);
      const float f1 = lds32f(sb + SMX_OFF + 512 + (32 + lane) * 4), f2 = lds32f(sb + SMX_OFF + 512 + (64 + lane) * 4), f3 = lds32f(sb + SMX_OFF + 512 + (96 + lane) * 4);
      const float mm = funkey((int)lds32(sb + SMX_OFF + (96 + lane) * 4));
      float l = (lp[0] + lp[1]) + (lp[2] + lp[3]);
      l = l * f1 + ((lp[4] + lp[5]) + (lp[6] + lp[7]));
      l = l * f2 + ((lp[8] + lp[9]) + (lp[10] + lp[11]));
      l = l * f3 + ((lp[12] + lp[13]) + (lp[14] + lp[15]));
      stg_rlx64(m0, tagf(l, 1u), __float_as_uint(mm));
      stg_rlx64(m1, tagf(l, 1u), __float_as_uint(mm));
    }
    if (cta < NFFN) {
      const unsigned par = epoch & 1u;
      if (hf == 0 && cta < 72) {
        const char* pa = G + MOD2_G + (cta * 32 + lane) * 4;
        unsigned v = ldg_rlx32(pa);
        poll32_fin(pa, par, v);
        sts32(sb + ST_OFF + 512 + lane * 4, v);
        __syncwarp();
        if (lane == 0) mbar_arrive(bars + 8 * B_GA);
      }
      uint32_t pk[2][9][2];
#pragma unroll
      for (int k = 0; k < 2; k++) {
        const char* pa = G + MOD2_G + ((k + 1) * 576 + ht) * 16;
        { unsigned v = ldg_rlx32(pa); poll32_fin(pa, par, v); }
#pragma unroll 1
        for (int it = 0; it < SPIN_LIMIT; it++) {
          uint4 a[9];
#pragma unroll
          for (int e = 0; e < 9; e++) a[e] = ldg_rlx(pa + e * 1024);
          bool ok = true;
#pragma unroll
          for (int e = 0; e < 9; e++) {
            ok = ok && ok4(a[e], par);
            pk[k][e][0] = pack_bf16(UF(a[e].x), UF(a[e].y)); pk[k][e][1] = pack_bf16(UF(a[e].z), UF(a[e].w));
          }
          if (__all_sync(0xffffffffu, ok)) break;
          DELAY(300);
        }
      }
      mbar_wait(bars + 8 * B_UVF, 0);
#pragma unroll
      for (int e = 0; e < 9; e++) sts128(sb + SC_OFF + (e * 64 + ht) * 16, make_uint4(pk[0][e][0], pk[0][e][1], pk[1][e][0], pk[1][e][1]));
      __syncwarp();
      if (lane == 0) mbar_arrive(bars + 8 * B_SC);
      if (hf == 0 && cta < 72) {
        const char* pa = G + MOD2_G + (3 * 2304 + cta * 32 + lane) * 4;
        unsigned v = ldg_rlx32(pa);
        poll32_fin(pa, par, v);
        sts32(sb + ST_OFF + 640 + lane * 4, v);
        __syncwarp();
        if (lane == 0) mbar_arrive(bars + 8 * B_GB);
      }
    }
    __syncwarp();
    asm volatile("barrier.cluster.wait.aligned;" ::: "memory");
    return;
  }
  if (warp == 16) {
    if (cta < 128) asm volatile("barrier.cluster.arrive.relaxed.aligned;" ::: "memory");
    uint64_t pol;
    asm volatile("createpolicy.fractional.L2::evict_first.b64 %0, 1.0;" : "=l"(pol));
    if (cta < 128) {
      const int h = cta >> 2, j = cta & 3;
      const unsigned ts = t0 + (((((cta >> 1) * 37) & 63) * TN(STAG)) >> 6);
      if (lane == 0) {
        mbar_arrive(bars + 8 * B_DONE);
#pragma unroll
        for (int c = 0; c < 3; c++) {
          while ((int)(gtime32() - ts) < TN(PACE_T0) + c * (9 * TN(PACE_A) >> 10)) ;
          mbar_expect_tx(bars + 8 * c, 9216);
          tma3d(sb + Y1_OFF + (c & 1) * 18432 + (c >> 1) * 9216, &M.wq, 0, j * 144 + (c >> 1) * 72, h * 2 + (c & 1), bars + 8 * c, pol);
        }
      }
      __syncwarp();
      int nst = 0;
      const int lim = cta < NFFN ? 255 : B_GU;
#pragma unroll 1
      for (int q = 0; q < 2; q++) {
        const uint32_t x = q ? se1.x : se0.x;
        const int id = x & 255, wb = (x >> 8) & 255, fb = (x >> 16) & 255;
        int map, c0 = 0, c1, c2, dst, b256;
        if (id < B_CKV || (id >= B_WUV && id < B_WO)) {
          const int c = id & 3, wq_ = id < B_WUK;
          map = wq_ ? 0 : (id < B_CKV ? 1 : 3);
          c2 = h * 2 + (c & 1);
          c1 = wq_ ? j * 144 + (c >> 1) * 72 : j * 128 + (c >> 1) * 64;
          dst = (map == 1 ? Y2_OFF : Y1_OFF) + (wq_ ? (c & 1) * 18432 + (c >> 1) * 9216 : (c & 1) * 16384 + (c >> 1) * 8192);
          b256 = wq_ ? 36 : 32;
        } else if (id < B_WUV) {
          const int c = id - B_CKV;
          map = 2; c2 = (cta & 1) * 4 + (c & 3); c1 = (cta >> 1) * 256 + (c >> 2) * 64; dst = X_OFF + c * 8192; b256 = 32;
        } else if (id < B_GU) {
          const int c = id - B_WO;
          map = 4; c2 = c * 3; c1 = cta * 32; dst = WO_OFF + c * 12288; b256 = 48;
        } else if (id < B_DN) {
          const int c = id - B_GU;
          map = c < 6 ? 5 : 6; c0 = cta * 40; c2 = 0; c1 = (c < 6 ? c : c - 6) * 96; dst = GA_OFF + c * 7680; b256 = 30;
        } else {
          const int c = id - B_DN;
          map = 7; c2 = c * 3; c1 = cta * 40 + (c & 0); dst = DN_OFF + c * 15360; b256 = 60;
        }
        const uint32_t bar = bars + 8 * id, wbar = bars + 8 * (wb < lim ? wb : B_DONE), fbar = bars + 8 * (fb != 255 ? fb : B_DONE);
        const int step = q * 32 + lane;
        const bool use = step >= 3 && step < NSTEP && id < lim;
        const unsigned um = __ballot_sync(0xffffffffu, use);
        if (use) {
          const uint32_t ta = sb + TAB_OFF + (nst + __popc(um & ((1u << lane) - 1u))) * 32;
          sts128(ta, make_uint4(sb + dst, bar, c0 | (c2 << 16), c1));
          sts128(ta + 16, make_uint4(wbar, fbar, ts + (q ? se1.y : se0.y), (b256 << 8) | (map << 23)));
        }
        nst += __popc(um);
      }
      __syncwarp();
      if (lane == 0) {
        uint4 ea = lds128(sb + TAB_OFF), eb = lds128(sb + TAB_OFF + 16);
#pragma unroll 1
        for (int n = 1; n <= nst; n++) {
          const uint4 na = lds128(sb + TAB_OFF + n * 32), nb = lds128(sb + TAB_OFF + n * 32 + 16);
          mbar_wait2(eb.x, eb.y);
          while ((int)(gtime32() - eb.z) < 0) ;
          mbar_expect_tx(ea.y, eb.w & 0xFFFF);
          tma3d(ea.x, (const CUtensorMap*)((const char*)&M.wq + (eb.w >> 16)), ea.z & 0xFFFF, ea.w, ea.z >> 16, ea.y, pol);
          ea = na; eb = nb;
        }
      }
    } else {
      if (lane == 0) {
#pragma unroll 1
        for (int k = 0; k < 11; k++) mbar_init(bars + 8 * (B_EMPTY + k), 9);
        WAIT_UNTIL(TN(MOD2_DELAY));
        const int q = cta - 128;
        int slot = 0, ph = 0, grp = 0, kc = 0;
#pragma unroll 1
        for (int n = 0; n < 36; n++) {
          if (n >= 11) mbar_wait(bars + 8 * (B_EMPTY + slot), ph ^ 1);
          WAIT_UNTIL(TN(MOD2_DELAY) + n * TN(MOD2_STEP));
          mbar_expect_tx(bars + 8 * slot, 18432);
          tma3d(sb + slot * 18432, &M.mod2, 1152 + grp * 576 + q * 144, kc * 64, 0, bars + 8 * slot, pol);
          if (++slot == 11) { slot = 0; ph ^= 1; }
          if (++kc == 9) { kc = 0; grp++; }
        }
      }
    }
    __syncwarp();
    if (cta < 128) asm volatile("barrier.cluster.wait.aligned;" ::: "memory");
    return;
  }

  char* const G = A.box;
  const int lo = g * 4 + t * 2;

  if ((cta < 72 || cta >= 128) && tid < 288) {
    int b = tid / 72, k = (tid % 72) * 8;
    uint4 o;
    o.x = pack_bf16(silu(bf_lo(cx.x)), silu(bf_hi(cx.x))); o.y = pack_bf16(silu(bf_lo(cx.y)), silu(bf_hi(cx.y)));
    o.z = pack_bf16(silu(bf_lo(cx.z)), silu(bf_hi(cx.z))); o.w = pack_bf16(silu(bf_lo(cx.w)), silu(bf_hi(cx.w)));
    sts128(sb + ACT_OFF + b * ACT_P + k * 2, o);
  }
  KEEP(par);
  const unsigned epoch = par + 1u;
  par = epoch & 1u;

  if (cta >= 128) {
    bar_sync(1, 512);
    if (warp < 9) {
      const int q = cta - 128;
      int slot = 0, ph = 0;
      const uint32_t aoff = ((lane >> 4) * 8 + (lane & 7)) * 288 + (warp * 16 + ((lane >> 3) & 1) * 8) * 2;
      const uint32_t boff = sb + ACT_OFF + (lane & 3) * ACT_P + (lane >> 3) * 16;
#pragma unroll 1
      for (int grp = 0; grp < 4; grp++) {
        float d0[4] = {0, 0, 0, 0}, d1[4] = {0, 0, 0, 0};
#pragma unroll 1
        for (int kc = 0; kc < 9; kc++) {
          mbar_wait(bars + 8 * slot, ph);
          uint32_t a[4][4], b[2][4];
#pragma unroll
          for (int e = 0; e < 4; e++) ldsm4t(a[e], sb + slot * 18432 + aoff + e * 16 * 288);
          ldsm4(b[0], boff + kc * 128); ldsm4(b[1], boff + kc * 128 + 64);
          mma16(d0, a[0], b[0][0], b[0][1]); mma16(d1, a[1], b[0][2], b[0][3]);
          mma16(d0, a[2], b[1][0], b[1][1]); mma16(d1, a[3], b[1][2], b[1][3]);
          __syncwarp();
          if (lane == 0) mbar_arrive(bars + 8 * (B_EMPTY + slot));
          if (++slot == 11) { slot = 0; ph ^= 1; }
        }
        TS(1 + grp);
        if (t < 2) {
          char* dst = G + MOD2_G + ((grp * 576 + q * 144 + warp * 16) * 4 + lo) * 4;
          stg_rlx64(dst, tagf(d0[0] + d1[0], par), tagf(d0[1] + d1[1], par));
          stg_rlx64(dst + 128, tagf(d0[2] + d1[2], par), tagf(d0[3] + d1[3], par));
        }
        __syncwarp();
      }
    }
    return;
  }

  const int h = cta >> 2, j = cta & 3, pr = cta >> 1, rk = cta & 1, bb = cta >> 5;

  if (tid < 288) sts128(sb + Y3_OFF + tid * 16, xx);
  bar_sync(1, 512);
  TS(1);

  if (warp < 12) {
    if (cta < 72) {
      float d[4] = {0, 0, 0, 0}, e[4] = {0, 0, 0, 0}, f[4] = {0, 0, 0, 0};
      const uint32_t aoff = sb + M1_OFF + ((lane >> 3) & 1) * 9216 + (warp * 48 + (lane >> 4) * 8 + (lane & 7)) * 16;
      const uint32_t boff = sb + ACT_OFF + (g & 3) * ACT_P + warp * 96 + t * 4;
      uint32_t a[3][4], b[6];
#pragma unroll
      for (int ks = 0; ks < 6; ks++) b[ks] = lds32(boff + ks * 16);
      asm volatile("cp.async.wait_all;" ::: "memory");
      __syncwarp();
#pragma unroll
      for (int ks = 0; ks < 3; ks++) ldsm4t(a[ks], aoff + ks * 256);
      mma16(d, a[0], b[0], b[1]); mma16(e, a[1], b[2], b[3]); mma16(f, a[2], b[4], b[5]);
      sts64f(sb + RED_OFF + (warp * 64 + (t >> 1) * 32 + g * 4 + (t & 1) * 2) * 4,
             t < 2 ? d[0] + e[0] + f[0] : d[2] + e[2] + f[2], t < 2 ? d[1] + e[1] + f[1] : d[3] + e[3] + f[3]);
      bar_sync(2, 384);
      if (warp < 4) {
        float v[12];
#pragma unroll
        for (int w = 0; w < 12; w++) v[w] = lds32f(sb + RED_OFF + (w * 64 + (tid & 63)) * 4);
        float s = ((v[0] + v[1]) + (v[2] + v[3])) + ((v[4] + v[5]) + (v[6] + v[7])) + ((v[8] + v[9]) + (v[10] + v[11]));
        stg_rlx32(G + (U_MOD1 + ((cta % 36) / 9) * 2 + cta / 36) * 8192 + (tid >> 6) * 4096 + (cta % 9) * 256 + (tid & 63) * 4, tagf(s, par));
      }
    }
  } else {
    const int b = warp - 12;
    float v[18], s = 0.f;
#pragma unroll
    for (int i = 0; i < 9; i++) {
      uint32_t w = lds32(sb + Y3_OFF + b * 1152 + (i * 32 + lane) * 4);
      v[2 * i] = bf_lo(w); v[2 * i + 1] = bf_hi(w); s += v[2 * i] + v[2 * i + 1];
    }
#pragma unroll
    for (int o = 16; o; o >>= 1) s += __shfl_xor_sync(0xffffffffu, s, o);
    const float mean = s * (1.f / 576.f);
    float q = 0.f;
#pragma unroll
    for (int i = 0; i < 18; i++) { float dd = v[i] - mean; q += dd * dd; }
#pragma unroll
    for (int o = 16; o; o >>= 1) q += __shfl_xor_sync(0xffffffffu, q, o);
    if (lane == 0) sts64f(sb + ST_OFF + b * 8, mean, rsqrtf(q * (1.f / 576.f) + 1e-5f));
  }
  float xres = 0.f;
  if (warp == 0 && cta < 72) {
    uint32_t w = lds32(sb + Y3_OFF + t * 1152 + ((cta * 8 + g) >> 1) * 4);
    xres = (g & 1) ? bf_hi(w) : bf_lo(w);
  }
  bar_sync(1, 512);
  TS(2);

  {
    const uint4 z = make_uint4(par ^ 1u, 0, par ^ 1u, 0);
    if (warp < 8) stg_rlx(G + (U_Q + h * 2 + (tid >> 7)) * 8192 + ((tid >> 6) & 1) * 4096 + j * 1024 + (tid & 63) * 16, z);
    else if (warp >= 13) {
      if (warp < 15) {
        const int u = tid - 416;
        char* d = G + (U_QA + ((u >> 4) * 2 + (j >> 1)) * 4 + (h >> 3)) * 8192 + (h & 7) * 512 + (j & 1) * 256 + (u & 15) * 16;
        stg_rlx(d, z); stg_rlx(d + 4096, z);
      } else if (cta < 72 && lane < 16) stg_rlx(G + (U_X2 + cta / 24) * 8192 + (lane >> 3) * 4096 + (cta % 24) * 128 + (lane & 7) * 16, z);
      __syncwarp();
    }
  }
  int p0 = (int)lds32(sb + ST_OFF + 64) & 1;
#define NEAR(u) (G + (u) * 8192 + (TN(NUMA) ? ((orient(u) ^ p0) << 12) : 0))

  uint32_t afr[9][4];
  if (warp < 8) {
    mbar_wait4(bars + 8 * B_WQ, bars + 8 * B_WQ + 8, bars + 8 * B_WQ + 16, bars + 8 * B_WQ + 24);
    const int ch = (warp & 3) * 2 + ((lane >> 3) & 1), row = (lane >> 4) * 8 + (lane & 7);
    const uint32_t a = sb + Y1_OFF + (warp >> 2) * 18432 + row * 128 + ((ch ^ (lane & 7)) << 4);
#pragma unroll
    for (int ks = 0; ks < 9; ks++) ldsm4t(afr[ks], a + ks * 2048);
  } else if (warp < 13) {
    const int k = min(tid - 256, 143), col = j * 144 + k;
    float nx[4];
#pragma unroll
    for (int b = 0; b < 4; b++) {
      uint32_t w = lds32(sb + Y3_OFF + b * 1152 + (col >> 1) * 4);
      uint2 st = lds64(sb + ST_OFF + b * 8);
      nx[b] = (((col & 1) ? bf_hi(w) : bf_lo(w)) - UF(st.x)) * UF(st.y);
    }
    uint32_t sa_ = sb + AC2_OFF + k * 2;
    KEEP(sa_);
    uint4 sa, ca;
    WAIT_UNTIL(TN(T_E1));
    p0 = (int)lds32(sb + ST_OFF + 64) & 1;
    poll16x2<true>(NEAR(U_MOD1 + j * 2) + k * 16, NEAR(U_MOD1 + j * 2 + 1) + k * 16, par, sa, ca, TN(TH1));
    sts16(sa_, to_bf16(nx[0] * (1.f + UF(ca.x)) + UF(sa.x)));
    sts16(sa_ + AC2_P, to_bf16(nx[1] * (1.f + UF(ca.y)) + UF(sa.y)));
    sts16(sa_ + 2 * AC2_P, to_bf16(nx[2] * (1.f + UF(ca.z)) + UF(sa.z)));
    sts16(sa_ + 3 * AC2_P, to_bf16(nx[3] * (1.f + UF(ca.w)) + UF(sa.w)));
  }
  uint32_t bo0 = sb + AC2_OFF + (lane & 3) * AC2_P + (lane >> 3) * 16;
  {
    char* dst = G + (U_Q + h * 2 + ((warp >> 2) & 1)) * 8192 + (t >> 1) * 4096 + j * 1024 + ((warp & 3) * 16 + g) * 16 + (t & 1) * 8;
    KEEP(bo0); KEEPL(dst);
    bar_sync(1, 512);
    TS(3);

    if (warp < 8) {
      float d0[4] = {0, 0, 0, 0}, d1[4] = {0, 0, 0, 0}, d2[4] = {0, 0, 0, 0};
      uint32_t b[5][4];
#pragma unroll
      for (int q = 0; q < 4; q++) ldsm4(b[q], bo0 + q * 64);
      ldsm4(b[4], bo0 + 256 - (lane >> 4) * 32);
#pragma unroll
      for (int ks = 0; ks < 9; ks += 3) {
        mma16(d0, afr[ks], b[ks >> 1][(ks & 1) * 2], b[ks >> 1][(ks & 1) * 2 + 1]);
        mma16(d1, afr[ks + 1], b[(ks + 1) >> 1][((ks + 1) & 1) * 2], b[(ks + 1) >> 1][((ks + 1) & 1) * 2 + 1]);
        mma16(d2, afr[ks + 2], b[(ks + 2) >> 1][((ks + 2) & 1) * 2], b[(ks + 2) >> 1][((ks + 2) & 1) * 2 + 1]);
      }
      stg_rlx64(dst, tagf(d0[0] + d1[0] + d2[0], par), __float_as_uint(d0[1] + d1[1] + d2[1]));
      stg_rlx64(dst + 128, tagf(d0[2] + d1[2] + d2[2], par), __float_as_uint(d0[3] + d1[3] + d2[3]));
    } else {
      mbar_wait4(bars + 8 * B_WUK, bars + 8 * B_WUK + 8, bars + 8 * B_WUK + 16, bars + 8 * B_WUK + 24);
      const int rho = lane & 7;
      const int row = (warp - 8) * 16 + 4 * (rho >> 1) + 2 * ((lane >> 3) & 1) + (rho & 1);
      const uint32_t a = sb + Y2_OFF + row * 128;
#pragma unroll
      for (int ks = 0; ks < 8; ks++) ldsm4(afr[ks], a + (ks >> 2) * 16384 + ((((ks & 3) * 2 + (lane >> 4)) ^ (row & 7)) << 4));
    }
  }
  if (lane == 0) mbar_arrive(bars + 8 * B_QDONE);
  __syncwarp();
  TS(4);

  p0 = (int)lds32(sb + ST_OFF + 64) & 1;
  {
    char* dst = G + (U_QA + ((g & 3) * 2 + (j >> 1)) * 4 + (h >> 3)) * 8192 + (g >> 2) * 4096 + (h & 7) * 512 + (j & 1) * 256 + (warp & 7) * 32 + t * 8;
    KEEPL(dst);
    if (warp < 8) {
      const int d = warp * 8 + g;
      const char* src0 = NEAR(U_Q + h * 2) + t * 1024 + d * 16;
      const char* src1 = NEAR(U_Q + h * 2 + 1) + t * 1024 + d * 16;
      uint32_t sa_ = sb + AC2_OFF + (4 + t) * AC2_P + d * 2;
      KEEP(sa_);
      uint4 v0, v1;
      DELAY(TN(D_E2));
      poll16x2<false>(src0, src1, par, v0, v1, TN(TH2));
      const float s0 = xreduce4<2, 1>(UF(v0.x), UF(v0.y), UF(v0.z), UF(v0.w), lane);
      const float s1 = xreduce4<2, 1>(UF(v1.x), UF(v1.y), UF(v1.z), UF(v1.w), lane);
      sts16(sa_, to_bf16(s0));
      sts16(sa_ + 128, to_bf16(s1));
    }
    bar_sync(1, 512);
    TS(5);

    if (warp >= 8) {
      float d0[4] = {0, 0, 0, 0}, d1[4] = {0, 0, 0, 0}, d2[4] = {0, 0, 0, 0}, d3[4] = {0, 0, 0, 0};
      uint32_t b[4][4];
#pragma unroll
      for (int q = 0; q < 4; q++) ldsm4(b[q], bo0 + 4 * AC2_P + q * 64);
#pragma unroll
      for (int q = 0; q < 4; q += 2) {
        mma16(d0, afr[2 * q], b[q][0], b[q][1]);
        mma16(d1, afr[2 * q + 1], b[q][2], b[q][3]);
        mma16(d2, afr[2 * q + 2], b[q + 1][0], b[q + 1][1]);
        mma16(d3, afr[2 * q + 3], b[q + 1][2], b[q + 1][3]);
      }
      const float sc = 0.08838834764831845f * 1.4426950408889634f;
      uint32_t p0 = pack_bf16(((d0[0] + d1[0]) + (d2[0] + d3[0])) * sc, ((d0[1] + d1[1]) + (d2[1] + d3[1])) * sc);
      uint32_t p1 = pack_bf16(((d0[2] + d1[2]) + (d2[2] + d3[2])) * sc, ((d0[3] + d1[3]) + (d2[3] + d3[3])) * sc);
      uint32_t q0, q1;
      asm volatile("movmatrix.sync.aligned.m8n8.trans.b16 %0, %1;" : "=r"(q0) : "r"(p0));
      asm volatile("movmatrix.sync.aligned.m8n8.trans.b16 %0, %1;" : "=r"(q1) : "r"(p1));
      stg_rlx64(dst, tagb(q0, par), q1);
      TSW(24, 480);
    }
  }
  asm volatile("barrier.cluster.arrive.relaxed.aligned;" ::: "memory");
  TS(6);

  {
    const int hd = tid >> 4, u = tid & 15;
    const char* src = NEAR(U_QA + (bb * 2 + rk) * 4 + (hd >> 3)) + (hd & 7) * 512 + u * 16;
    uint32_t a = sb + Y3_OFF + (u >> 3) * 4096 + hd * 128 + (((u & 7) ^ (hd & 7)) << 4);
    KEEP(a);
    DELAY(TN(D_E3));
    uint4 v0, v1;
    poll16x2<false>(src, src + 256, par, v0, v1, TN(TH3));
    v0.x &= ~1u; v0.z &= ~1u; v1.x &= ~1u; v1.z &= ~1u;
    sts128(a, v0);
    sts128(a + 8192, v1);
    fence_async();
    __syncwarp();
  }
  asm volatile("barrier.cluster.wait.aligned;" ::: "memory");
  bar_sync(1, 512);
  TS(7);

  {
    const int wg = warp >> 2, wq = warp & 3, tl = tid & 127;
    float acc[16];
#pragma unroll
    for (int e = 0; e < 16; e++) acc[e] = 0.f;
    const uint32_t rbuf = sb + Y2_OFF + wg * 8192;
    float s[16], ls[8];
    const uint32_t fa = sb + SMX_OFF + 512 + 2 * t * 4;
    const uint64_t dpa = mkdesc(sb + X_OFF + wg * 8192, 1024, 1), dpb = mkdesc(sb + Y2_OFF, 512, 2);
    auto pv_issue = [&](int i) {
      const uint64_t da = dpa + i * 2048, db = dpb + i * 512;
      mbar_wait(bars + 8 * (B_PRDY + i), 0);
      uint2 f[4];
#pragma unroll
      for (int q = 0; q < 4; q++) f[q] = lds64(fa + i * 128 + q * 32);
#pragma unroll
      for (int q = 0; q < 4; q++) { acc[4 * q] *= UF(f[q].x); acc[4 * q + 1] *= UF(f[q].y); acc[4 * q + 2] *= UF(f[q].x); acc[4 * q + 3] *= UF(f[q].y); }
      wg_fence();
#pragma unroll
      for (int ks = 0; ks < 4; ks++) wgmma_n32<1, 1>(acc, da + ks * 128, db + ks * 64, 1);
      wg_commit();
    };
    auto pv_done = [&](int i) { wg_wait0(); if (lane == 0) mbar_arrive(bars + 8 * (B_TFREE + i)); };
#pragma unroll 1
    for (int i = 0; i < wg - 1; i++) { mbar_wait(bars + 8 * (B_CKV + i * 4 + wg), 0); pv_issue(i); pv_done(i); }
    {
      uint32_t rem, rbar;
      asm volatile("mapa.shared::cluster.u32 %0, %1, %2;" : "=r"(rem) : "r"(rbuf + tl * 16), "r"(rk ^ 1));
      asm volatile("mapa.shared::cluster.u32 %0, %1, %2;" : "=r"(rbar) : "r"(bars + 8 * (B_SRECV + wg)), "r"(rk ^ 1));
#pragma unroll
      for (int e = 0; e < 16; e++) s[e] = 0.f;
#pragma unroll
      for (int sl = 0; sl < 4; sl++) {
        const uint64_t da = mkdesc(sb + X_OFF + (wg * 4 + sl) * 8192, 1024, 1);
        const uint64_t db = mkdesc(sb + Y3_OFF + sl * 4096, 1024, 1);
        mbar_wait(bars + 8 * (B_CKV + wg * 4 + sl), 0);
        wg_fence();
#pragma unroll
        for (int kk = 0; kk < 4; kk++) wgmma_n32<0, 0>(s, da + kk * 2, db + kk * 2, 1);
        wg_commit();
      }
      wg_wait0();
      FA(0);
#pragma unroll
      for (int q = 0; q < 4; q++)
        asm volatile("st.async.shared::cluster.mbarrier::complete_tx::bytes.v4.f32 [%0], {%1,%2,%3,%4}, [%5];"
                     :: "r"(rem + q * 2048), "f"(s[4 * q]), "f"(s[4 * q + 1]), "f"(s[4 * q + 2]), "f"(s[4 * q + 3]), "r"(rbar) : "memory");
      TSW(16 + wg, wg * 128);
    }
    if (wg > 0) { mbar_wait(bars + 8 * (B_CKV + wg * 5 - 4), 0); pv_issue(wg - 1); pv_done(wg - 1); }
    const int myhead = (lane & 24) + 2 * t + (g & 1);
    uint32_t oa0 = 0, oa1 = 0;
    auto dests = [&]() {
      mbar_wait(bars + 8 * B_MASK, 0);
      const int c0 = (tl >> 3) * 4 + rk * 2 + (wg >> 1);
      oa0 = BLK_G + c0 * 65536 + bb * 16384 + (hsel(sb, c0) << 12) + (pr & 15) * 256 + (wg & 1) * 128 + (tl & 7) * 16;
      oa1 = BLK_G + (c0 + 64) * 65536 + bb * 16384 + (hsel(sb, c0 + 64) << 12) + (pr & 15) * 256 + (wg & 1) * 128 + (tl & 7) * 16;
    };
    if (wg == 3) dests();
    {
      const uint32_t amax = sb + SMX_OFF + (wg * 32 + myhead) * 4, amx2 = sb + SMX_OFF + (wg * 32 + 2 * t) * 4;
      const uint32_t pb = rbuf + (wq * 16 + g) * 64 + t * 4 + ((g >> 1) << 4), rb = rbuf + tl * 16;
      const int kprev = wg > 0 ? (int)lds32(amax - 128) : (int)0x80000000;
      FA(1);
      mbar_wait(bars + 8 * (B_SRECV + wg), 0);
      FA(2);
      float mx[8];
      {
        uint4 v[4];
#pragma unroll
        for (int q = 0; q < 4; q++) v[q] = lds128(rb + q * 2048);
#pragma unroll
        for (int q = 0; q < 4; q++) {
          s[4 * q] += UF(v[q].x); s[4 * q + 1] += UF(v[q].y); s[4 * q + 2] += UF(v[q].z); s[4 * q + 3] += UF(v[q].w);
          mx[2 * q] = fmaxf(s[4 * q], s[4 * q + 2]); mx[2 * q + 1] = fmaxf(s[4 * q + 1], s[4 * q + 3]);
        }
      }
      const int key = max(fkey(xreduce8<true>(mx, lane)), kprev);
      asm volatile("red.shared.max.s32 [%0], %1;" :: "r"(amax), "r"(key) : "memory");
      bar_sync(4 + wg, 128);
      FA(3);
      uint2 mk[4];
#pragma unroll
      for (int q = 0; q < 4; q++) mk[q] = lds64(amx2 + q * 32);
      const int kcur = (int)lds32(amax);
      const float fac = wg > 0 ? ex2(funkey(kprev) - funkey(kcur)) : 0.f;
      uint32_t pk[8];
#pragma unroll
      for (int q = 0; q < 4; q++) {
        const float m0 = funkey((int)mk[q].x), m1 = funkey((int)mk[q].y);
        const float p0 = ex2(s[4 * q] - m0), p1 = ex2(s[4 * q + 1] - m1), p2 = ex2(s[4 * q + 2] - m0), p3 = ex2(s[4 * q + 3] - m1);
        pk[2 * q] = pack_bf16(p0, p1); pk[2 * q + 1] = pack_bf16(p2, p3);
        ls[2 * q] = p0 + p2; ls[2 * q + 1] = p1 + p3;
      }
      sts32f(amax + 512, fac);
#pragma unroll
      for (int q = 0; q < 4; q++) { sts32(pb ^ (q << 4), pk[2 * q]); sts32((pb ^ (q << 4)) + 512, pk[2 * q + 1]); }
      fence_async();
      __syncwarp();
      if (lane == 0) mbar_arrive(bars + 8 * (B_PRDY + wg));
      FA(4);
    }
    pv_issue(wg);
    FA(5);
    sts32f(sb + RED_OFF + (warp * 32 + myhead) * 4, xreduce8<false>(ls, lane));
    __syncwarp();
    if (lane == 0) mbar_arrive(bars + 8 * B_LRDY);
    if (wg < 3) {
      pv_done(wg);
#pragma unroll 1
      for (int i = wg + 1; i < 3; i++) { mbar_wait(bars + 8 * (B_CKV + i * 4 + wg), 0); pv_issue(i); pv_done(i); }
      dests();
      mbar_wait(bars + 8 * (B_CKV + 12 + wg), 0);
      pv_issue(3);
    }
    pv_done(3);
    TS(8);
    FA(6);
    const uint32_t stg = sb + Y3_OFF + wg * 4096;
#pragma unroll
    for (int hf = 0; hf < 2; hf++) {
      uint32_t r0 = pack_bf16(acc[2 * hf], acc[2 * hf + 1]), r1 = pack_bf16(acc[4 + 2 * hf], acc[5 + 2 * hf]);
      uint32_t r2 = pack_bf16(acc[8 + 2 * hf], acc[9 + 2 * hf]), r3 = pack_bf16(acc[12 + 2 * hf], acc[13 + 2 * hf]);
      const uint32_t a = stg + lane * 128 + (((wq * 2 + hf) ^ (lane & 7)) << 4);
      asm volatile("stmatrix.sync.aligned.m8n8.x4.trans.shared.b16 [%0], {%1,%2,%3,%4};" :: "r"(a), "r"(r0), "r"(r1), "r"(r2), "r"(r3) : "memory");
    }
    bar_sync(4 + wg, 128);
    {
      const int hd = tl >> 3, ch = tl & 7;
      uint4 v0 = lds128(stg + hd * 128 + ((ch ^ (hd & 7)) << 4)), v1 = lds128(stg + 2048 + hd * 128 + ((ch ^ (hd & 7)) << 4));
      v0.x = tagb(v0.x, 1u); v0.z = tagb(v0.z, 1u); v1.x = tagb(v1.x, 1u); v1.z = tagb(v1.z, 1u);
      stg_rlx(G + oa0, v0);
      stg_rlx(G + oa1, v1);
    }
    __syncwarp();
    if (lane == 0) mbar_arrive(bars + 8 * B_ADONE);
    __syncwarp();
  }
  TS(9);
  FA(7);

  uint32_t auv[8][4];
  if (warp < 8) {
    mbar_wait4(bars + 8 * B_WUV, bars + 8 * B_WUV + 8, bars + 8 * B_WUV + 16, bars + 8 * B_WUV + 24);
    const int ch = (warp & 3) * 2 + ((lane >> 3) & 1), row = (lane >> 4) * 8 + (lane & 7);
    const uint32_t a = sb + Y1_OFF + (warp >> 2) * 16384 + row * 128 + ((ch ^ (lane & 7)) << 4);
#pragma unroll
    for (int ks = 0; ks < 8; ks++) ldsm4t(auv[ks], a + ks * 2048);
  }
  const uint32_t myh = hsel(sb, cta);
  char* const blk = G + BLK_G + cta * 65536;
  {
    const int b = warp >> 2, cq = warp & 3;
    const char* mlp = blk + 5 * 8192 + ((myh ^ 1u) << 12) + 2048 + (b * 16 + g) * 32;
    const char* src = blk + b * 16384 + (myh << 12) + g * 256 + cq * 64 + t * 16;
    uint32_t sa_ = sb + AC2_OFF + b * AC2_P + (cq * 32 + t * 8 + g) * 2;
    const int cc = h * 4 + ((warp >> 1) & 3);
    char* dst = G + BLK_G + cc * 65536 + 5 * 8192 + ((hsel(sb, cc) ^ 1u) << 12) + j * 512 + ((warp & 1) * 16 + (t >> 1) * 8 + g) * 16 + (t & 1) * 8;
    KEEP(sa_); KEEPL(src); KEEPL(dst);
    DELAY(TN(D_E4));
    uint2 ml0 = make_uint2(0, 0), ml1 = ml0;
    uint4 v0 = make_uint4(0, 0, 0, 0), v1 = v0;
#pragma unroll 1
    for (int it = 0; it < SPIN_LIMIT; it++) {
      const bool b0 = !(v0.x & v0.z & 1u), b1 = !(v1.x & v1.z & 1u), c0 = !(ml0.x & 1u), c1 = !(ml1.x & 1u);
      const unsigned m0 = __ballot_sync(0xffffffffu, b0), m1 = __ballot_sync(0xffffffffu, b1);
      if (!(m0 | m1) && !__any_sync(0xffffffffu, c0 || c1)) break;
      if (__popc(m0) + __popc(m1) > TN(TH4)) poll_one(m0 ? src : src + 2048, __ffs(m0 ? m0 : m1) - 1, 1u);
      if (c0) ml0 = ldg_rlx64(mlp);
      if (c1) ml1 = ldg_rlx64(mlp + 256);
      ldg_rlx_if(b0, src, v0);
      ldg_rlx_if(b1, src + 2048, v1);
    }
    float mm = fmaxf(UF(ml0.y), UF(ml1.y));
#pragma unroll
    for (int o = 16; o >= 4; o >>= 1) mm = fmaxf(mm, __shfl_xor_sync(0xffffffffu, mm, o));
    const float w0 = ex2(UF(ml0.y) - mm), w1 = ex2(UF(ml1.y) - mm);
    float l = w0 * UF(ml0.x) + w1 * UF(ml1.x);
#pragma unroll
    for (int o = 16; o >= 4; o >>= 1) l += __shfl_xor_sync(0xffffffffu, l, o);
    v0.x &= ~1u; v0.z &= ~1u; v1.x &= ~1u; v1.z &= ~1u;
    float a[8];
    a[0] = w0 * bf_lo(v0.x) + w1 * bf_lo(v1.x); a[1] = w0 * bf_hi(v0.x) + w1 * bf_hi(v1.x);
    a[2] = w0 * bf_lo(v0.y) + w1 * bf_lo(v1.y); a[3] = w0 * bf_hi(v0.y) + w1 * bf_hi(v1.y);
    a[4] = w0 * bf_lo(v0.z) + w1 * bf_lo(v1.z); a[5] = w0 * bf_hi(v0.z) + w1 * bf_hi(v1.z);
    a[6] = w0 * bf_lo(v0.w) + w1 * bf_lo(v1.w); a[7] = w0 * bf_hi(v0.w) + w1 * bf_hi(v1.w);
    sts16(sa_, to_bf16(__fdividef(xreduce8<false>(a, lane), l)));
    bar_sync(1, 512);
    TS(10);

    if (warp < 8) {
      float d0[4] = {0, 0, 0, 0}, d1[4] = {0, 0, 0, 0}, d2[4] = {0, 0, 0, 0}, d3[4] = {0, 0, 0, 0};
      uint32_t bf[4][4];
#pragma unroll
      for (int q = 0; q < 4; q++) ldsm4(bf[q], bo0 + q * 64);
#pragma unroll
      for (int q = 0; q < 4; q += 2) {
        mma16(d0, auv[2 * q], bf[q][0], bf[q][1]);
        mma16(d1, auv[2 * q + 1], bf[q][2], bf[q][3]);
        mma16(d2, auv[2 * q + 2], bf[q + 1][0], bf[q + 1][1]);
        mma16(d3, auv[2 * q + 3], bf[q + 1][2], bf[q + 1][3]);
      }
      stg_rlx64(dst, tagf(t < 2 ? (d0[0] + d1[0]) + (d2[0] + d3[0]) : (d0[2] + d1[2]) + (d2[2] + d3[2]), 1u),
                __float_as_uint(t < 2 ? (d0[1] + d1[1]) + (d2[1] + d3[1]) : (d0[3] + d1[3]) + (d2[3] + d3[3])));
      if (lane == 0) mbar_arrive(bars + 8 * B_UVF);
      TSW(22, 224);
    }
  }
  uint32_t roff[3];
#pragma unroll
  for (int m = 0; m < 3; m++) {
    const int u = min((warp * 3 + m) * 2 + (t & 1), 71);
    roff[m] = BLK_G + u * 65536 + (1 + (cta >> 6) * 2) * 8192 + ((hsel(sb, u) ^ 1u) << 12) + (cta & 63) * 64 + g * 8;
  }
  const char* const rsrc = blk + (1 + (warp >> 3) * 2) * 8192 + ((myh ^ 1u) << 12) + (tid & 255) * 16;
  {
    uint32_t awo[6][4];
    if (warp < 12) {
      mbar_wait(bars + 8 * (B_WO + (warp >> 2)), 0);
      const int row = (lane >> 4) * 8 + (lane & 7);
#pragma unroll
      for (int m = 0; m < 3; m++) {
        const int mt = warp * 3 + m, ch = (mt & 3) * 2 + ((lane >> 3) & 1);
        const uint32_t a = sb + WO_OFF + (mt >> 2) * 4096 + row * 128 + ((ch ^ (lane & 7)) << 4);
        ldsm4t(awo[2 * m], a);
        ldsm4t(awo[2 * m + 1], a + 2048);
      }
    } else {
      const int dl = (warp - 12) * 8 + g;
      uint32_t sa_ = sb + AC2_OFF + (4 + t) * AC2_P + dl * 2;
      KEEP(sa_);
      DELAY(TN(D_E5));
      uint4 v = poll16<false>(blk + 5 * 8192 + ((myh ^ 1u) << 12) + t * 512 + dl * 16, 1u, TN(TH5));
      TSW(23, 384);
      sts16(sa_, to_bf16(xreduce4<2, 1>(UF(v.x), UF(v.y), UF(v.z), UF(v.w), lane)));
    }
    bar_sync(1, 512);
    TS(11);

    if (warp < 12) {
      uint32_t bq[4];
      ldsm4(bq, bo0 + 4 * AC2_P);
      const uint32_t b0 = bq[0], b1 = bq[1], b2 = bq[2], b3 = bq[3];
      float d[3][4] = {{0, 0, 0, 0}, {0, 0, 0, 0}, {0, 0, 0, 0}};
#pragma unroll
      for (int m = 0; m < 3; m++) mma16(d[m], awo[2 * m], b0, b1);
#pragma unroll
      for (int m = 0; m < 3; m++) mma16(d[m], awo[2 * m + 1], b2, b3);
      send_pieces(G, roff, d, t, 1u);
    }
  }
  TS(12);
  if (cta >= NFFN) return;

  float x2res = 0.f;
  if (cta < 72) {
    char* dst = G + (U_X2 + cta / 24) * 8192 + (lane & 1) * 4096 + (cta % 24) * 128 + (lane >> 1) * 8;
    KEEPL(dst);
    DELAY(TN(D_E6));
    const float s = reduce_pieces(rsrc, 128, 1u, sb, warp, lane, TN(TH6));
    if (warp == 0) {
      mbar_wait(bars + 8 * B_GA, 0);
      x2res = xres + lds32f(sb + ST_OFF + 512 + lane * 4) * s;
      const float nb = __shfl_xor_sync(0xffffffffu, x2res, 1);
      stg_rlx64(dst, tagf((lane & 1) ? nb : x2res, par), __float_as_uint((lane & 1) ? x2res : nb));
    }
  } else {
    DELAY(TN(D_E7B));
  }
  TS(13);

  {
    const int gu_u = warp % 5, gu_t = warp / 5;
    uint32_t agu[12][4];
    const uint32_t bo = sb + ACT_OFF + (lane & 3) * ACT_P + (lane >> 3) * 16 + gu_t * 384 + ((lane >> 2) & 1) * 192;
    const uint32_t ra = sb + SC_OFF + 9216 + ((warp * 2 + (t >> 1)) * 64 + g * 4 + (t & 1) * 2) * 4;
    const uint32_t ga = sb + GA_OFF + ((lane >> 3) & 1) * 46080 + (gu_t * 192 + (lane >> 4) * 8 + (lane & 7)) * 80 + gu_u * 16;
    const uint32_t gb = bars + 8 * (B_GU + gu_t * 2);
    p0 = (int)lds32(sb + ST_OFF + 64) & 1;
    bool have_w = warp >= 15;
    if (warp >= 9 && warp < 15) mbar_wait4(gb, gb + 8, gb + 48, gb + 56);
    const char* x0 = NEAR(U_X2 + tid / 192) + (tid % 192) * 16;
    const char* x1 = NEAR(U_X2 + (tid + 288) / 192) + ((tid + 288) % 192) * 16;
    const char* xk = NEAR(U_X2);
    uint4 v0 = make_uint4(par ^ 1u, 0, 0, 0), v1 = v0, vk = v0;
    DELAY(TN(D_E7));
#pragma unroll 1
    for (int it = 0; it < SPIN_LIMIT; it++) {
      const bool b0 = warp < 9 && !ok2(v0, par), b1 = warp < 9 && !ok2(v1, par), bk = warp < 9 && !ok2(vk, par);
      const bool more = __any_sync(0xffffffffu, b0 || b1 || bk);
      const bool all = !bk || TN(TH7);
      ldg_rlx_if(b0 && all, x0, v0); ldg_rlx_if(b1 && all, x1, v1); ldg_rlx_if(bk, xk, vk);
      if (!have_w && (more || warp >= 9) && __all_sync(0xffffffffu, mbar_test4(gb, gb + 8, gb + 48, gb + 56))) {
        have_w = true;
#pragma unroll
        for (int ks = 0; ks < 12; ks++) ldsm4t(agu[ks], ga + ks * 1280);
      }
      if (!more) break;
    }
    if (warp < 9) {
      const uint32_t sa_ = sb + ACT_OFF + tid * 2, sp = sb + ST_OFF + 128 + (warp * 8 + g) * 4, sr = sb + ST_OFF + 128 + (lane & 7) * 4;
      TSW(29, 32);
      FB(0);
      const float xa[4] = {UF(v0.x) - UF(vk.x), UF(v0.y) - UF(vk.y), UF(v0.z) - UF(vk.z), UF(v0.w) - UF(vk.w)};
      const float xb[4] = {UF(v1.x) - UF(vk.x), UF(v1.y) - UF(vk.y), UF(v1.z) - UF(vk.z), UF(v1.w) - UF(vk.w)};
      float st[8];
#pragma unroll
      for (int b = 0; b < 4; b++) { st[2 * b] = xa[b] + xb[b]; st[2 * b + 1] = xa[b] * xa[b] + xb[b] * xb[b]; }
      float z = xreduce8<false>(st, lane);
      z += __shfl_xor_sync(0xffffffffu, z, 2);
      z += __shfl_xor_sync(0xffffffffu, z, 1);
      sts32f(sp, z);
      FB(1);
      mbar_wait(bars + 8 * B_SC, 0);
      const uint4 sc0 = lds128(sb + SC_OFF + tid * 16), sc1 = lds128(sb + SC_OFF + (288 + tid) * 16);
      const float sh0[4] = {bf_lo(sc0.x), bf_hi(sc0.x), bf_lo(sc0.y), bf_hi(sc0.y)}, sh1[4] = {bf_lo(sc1.x), bf_hi(sc1.x), bf_lo(sc1.y), bf_hi(sc1.y)};
      const float cs0[4] = {1.f + bf_lo(sc0.z), 1.f + bf_hi(sc0.z), 1.f + bf_lo(sc0.w), 1.f + bf_hi(sc0.w)};
      const float cs1[4] = {1.f + bf_lo(sc1.z), 1.f + bf_hi(sc1.z), 1.f + bf_lo(sc1.w), 1.f + bf_hi(sc1.w)};
      bar_sync(2, 288);
      FB(2);
      float pv[9];
#pragma unroll
      for (int w = 0; w < 9; w++) pv[w] = lds32f(sr + w * 32);
      float tot = (((pv[0] + pv[1]) + (pv[2] + pv[3])) + ((pv[4] + pv[5]) + (pv[6] + pv[7])) + pv[8]) * (1.f / 576.f);
      const float oth = __shfl_xor_sync(0xffffffffu, tot, 1);
      tot = (lane & 1) ? rsqrtf(fmaxf(tot - oth * oth, 0.f) + 1e-5f) : tot;
      float mean[4], rs[4];
#pragma unroll
      for (int b = 0; b < 4; b++) { mean[b] = __shfl_sync(0xffffffffu, tot, 2 * b); rs[b] = __shfl_sync(0xffffffffu, tot, 2 * b + 1); }
#pragma unroll
      for (int b = 0; b < 4; b++) {
        sts16(sa_ + b * ACT_P, to_bf16((xa[b] - mean[b]) * rs[b] * cs0[b] + sh0[b]));
        sts16(sa_ + b * ACT_P + 576, to_bf16((xb[b] - mean[b]) * rs[b] * cs1[b] + sh1[b]));
      }
      FB(3);
      if (!have_w) {
        mbar_wait4(gb, gb + 8, gb + 48, gb + 56);
#pragma unroll
        for (int ks = 0; ks < 12; ks++) ldsm4t(agu[ks], ga + ks * 1280);
      }
    }
    bar_sync(1, 512);
    TS(14);
    FB(4);

    if (warp < 15) {
      float d0[4] = {0, 0, 0, 0}, d1[4] = {0, 0, 0, 0}, d2[4] = {0, 0, 0, 0}, d3[4] = {0, 0, 0, 0};
      uint32_t b[3][4];
#pragma unroll
      for (int q = 0; q < 3; q++) ldsm4(b[q], bo + q * 64);
#pragma unroll
      for (int q = 0; q < 3; q++) {
        mma16(d0, agu[2 * q], b[q][0], b[q][1]);
        mma16(d1, agu[2 * q + 1], b[q][2], b[q][3]);
        mma16(d2, agu[6 + 2 * q], b[q][0], b[q][1]);
        mma16(d3, agu[7 + 2 * q], b[q][2], b[q][3]);
      }
      const bool lo_ = t < 2;
      sts64f(ra, lo_ ? d0[0] + d1[0] : d2[0] + d3[0], lo_ ? d0[1] + d1[1] : d2[1] + d3[1]);
      sts64f(ra + 128, lo_ ? d0[2] + d1[2] : d2[2] + d3[2], lo_ ? d0[3] + d1[3] : d2[3] + d3[3]);
    }
  }
  {
    uint32_t a8[3][2], adn[6][4];
    FB(5);
    if (warp < 11) asm volatile("bar.arrive 9, 512;" ::: "memory");
    else {
      bar_sync(9, 512);
      float v[12];
      const uint32_t ra = sb + SC_OFF + 9216 + ((warp - 11) * 128 + lane) * 4;
#pragma unroll
      for (int q = 0; q < 6; q++) v[q] = lds32f(ra + (q >> 1) * 2560 + (q & 1) * 256);
#pragma unroll
      for (int q = 0; q < 6; q++) v[6 + q] = lds32f(ra + (q >> 1) * 2560 + (q & 1) * 256 + 128);
      sts16(sb + AC2_OFF + t * AC2_P + ((warp - 11) * 8 + g) * 2,
            to_bf16(silu((v[0] + v[1]) + (v[2] + v[3]) + (v[4] + v[5])) * ((v[6] + v[7]) + (v[8] + v[9]) + (v[10] + v[11]))));
    }
    if (warp < 12) {
      mbar_wait(bars + 8 * (B_DN + (warp >> 2)), 0);
      const int row = (lane >> 4) * 8 + (lane & 7);
#pragma unroll
      for (int m = 0; m < 3; m++) {
        const int mt = warp * 3 + m, ch = (mt & 3) * 2 + ((lane >> 3) & 1);
        const uint32_t a = sb + DN_OFF + (mt >> 2) * 5120 + ((ch ^ (lane & 7)) << 4);
        ldsm4t(adn[2 * m], a + row * 128);
        ldsm4t(adn[2 * m + 1], a + row * 128 + 2048);
        ldsm2t(a8[m], a + (lane & 7) * 128 + 4096);
      }
    }
    FB(6);
    bar_sync(1, 512);
    TS(15);
    FB(7);

    if (warp < 12) {
      uint32_t bq[4], br[4];
      ldsm4(bq, bo0);
      ldsm4(br, bo0 + 64);
      const uint32_t b0 = bq[0], b1 = bq[1], b2 = bq[2], b3 = bq[3], b4 = br[0];
      float d[3][4] = {{0, 0, 0, 0}, {0, 0, 0, 0}, {0, 0, 0, 0}};
#pragma unroll
      for (int m = 0; m < 3; m++) mma16(d[m], adn[2 * m], b0, b1);
#pragma unroll
      for (int m = 0; m < 3; m++) mma16(d[m], adn[2 * m + 1], b2, b3);
#pragma unroll
      for (int m = 0; m < 3; m++) mma8(d[m], a8[m], b4);
      send_pieces(G, roff, d, t, 0u);
    }
  }
  TSW(20, 128);
  FB(8);

  if (cta < 72) {
    uint16_t* dst = (uint16_t*)A.out + t * 576 + cta * 8 + g;
    KEEPL(dst);
    DELAY(TN(D_E8));
    const float s = reduce_pieces(rsrc, NFFN, 0u, sb, warp, lane, TN(TH8));
    if (warp == 0) {
      mbar_wait(bars + 8 * B_GB, 0);
      *dst = to_bf16(x2res + lds32f(sb + ST_OFF + 640 + lane * 4) * s);
      if (cta == 0 && lane == 0) *(unsigned*)(G + EPOCH_G) = epoch;
    }
  }
  TS(21);
}

typedef CUresult (*EncFn)(CUtensorMap*, CUtensorMapDataType, cuuint32_t, void*, const cuuint64_t*, const cuuint64_t*,
                          const cuuint32_t*, const cuuint32_t*, CUtensorMapInterleave, CUtensorMapSwizzle,
                          CUtensorMapL2promotion, CUtensorMapFloatOOBfill);

static void make_map(EncFn f, CUtensorMap* m, void* p, uint64_t cols, uint64_t rows, uint64_t inner, uint32_t bc, uint32_t br, uint32_t bs, bool swz) {
  cuuint64_t gd[3] = {inner, rows, cols / inner};
  cuuint64_t gs[2] = {cols * 2, inner * 2};
  cuuint32_t bd[3] = {bc, br, bs};
  cuuint32_t es[3] = {1, 1, 1};
  f(m, CU_TENSOR_MAP_DATA_TYPE_BFLOAT16, 3, p, gd, gs, bd, es, CU_TENSOR_MAP_INTERLEAVE_NONE,
    swz ? CU_TENSOR_MAP_SWIZZLE_128B : CU_TENSOR_MAP_SWIZZLE_NONE, CU_TENSOR_MAP_L2_PROMOTION_L2_128B,
    CU_TENSOR_MAP_FLOAT_OOB_FILL_NONE);
}

extern "C" void kernel_launch(void* const* d_in, const int* in_sizes, int n_in, void* d_out, int out_size) {
  static EncFn enc = nullptr;
  static char* box = nullptr;
  if (!enc) {
    void* fn = nullptr;
    cudaDriverEntryPointQueryResult qr;
    cudaGetDriverEntryPoint("cuTensorMapEncodeTiled", &fn, cudaEnableDefault, &qr);
    enc = (EncFn)fn;
    cudaGetSymbolAddress((void**)&box, g_box);
    box = (char*)(((uintptr_t)box + 0x1FFFFF) & ~(uintptr_t)0x1FFFFF);
    cudaFuncSetAttribute(fused_kernel, cudaFuncAttributeMaxDynamicSharedMemorySize, SMEM_BYTES);
  }
  Maps M;
  make_map(enc, &M.wq, d_in[2], 4096, 576, 64, 64, 72, 1, true);
  make_map(enc, &M.wuk, d_in[3], 4096, 512, 64, 64, 64, 1, true);
  make_map(enc, &M.ckv, d_in[1], 512, 16384, 64, 64, 64, 1, true);
  make_map(enc, &M.wuv, d_in[4], 4096, 512, 64, 64, 64, 1, true);
  make_map(enc, &M.wo, d_in[5], 576, 4096, 64, 64, 32, 3, true);
  make_map(enc, &M.gate, d_in[7], 4608, 576, 4608, 40, 96, 1, false);
  make_map(enc, &M.up, d_in[8], 4608, 576, 4608, 40, 96, 1, false);
  make_map(enc, &M.down, d_in[9], 576, 4608, 64, 64, 40, 3, true);
  make_map(enc, &M.mod2, d_in[11], 3456, 576, 3456, 144, 64, 1, false);
  Prm A;
  A.x = (const bf16*)d_in[0];
  A.c = (const bf16*)d_in[10];
  A.wmod = (const bf16*)d_in[11];
  A.out = (bf16*)d_out;
  A.box = box;
  Sched S;
  {
    static const char* orders[] = {
      "uuuuoooggggggggggggddd",
      "uuuuoooggggdggggdggggd",
      "uuuuogogoggggdgggdgggd",
    };
    int seq[NSTEP], kb10[NSTEP], n = 0;
    for (int i = 0; i < B_WUV; i++) seq[n++] = i;
    int nu = 0, no = 0, ng = 0, nd = 0;
    const char* ord = orders[TN(ORDER)];
    for (const char* c = ord; *c && n < NSTEP; c++) {
      if (*c == 'u') seq[n++] = B_WUV + nu++;
      else if (*c == 'o') seq[n++] = B_WO + no++;
      else if (*c == 'g') seq[n++] = B_GU + ng++;
      else if (*c == 'd') seq[n++] = B_DN + nd++;
    }
    double tm = TN(PACE_T0);
    for (int i = 0; i < NSTEP; i++) {
      const int id = seq[i];
      kb10[i] = id < B_WUK ? 18 : id < B_WO ? 16 : id < B_GU ? 24 : id < B_DN ? 15 : 30;
      const int ph = i < B_CKV + 5 ? 0 : i < B_WUV ? 1 : (id < B_GU || i < B_GU) ? 2 : 3;
      const int win = ph == 0 ? TN(W_A) : ph == 1 ? TN(W_P) : ph == 2 ? TN(W_B) : TN(W_G);
      const int pace = id >= B_GU ? TN(PACE_G) : ph == 0 ? TN(PACE_A) : ph == 1 ? TN(PACE_PS) : TN(PACE_B);
      int k = i, sum = 0;
      while (k >= 0 && sum + kb10[k] <= 2 * win) sum += kb10[k--];
      const int wb = k >= 0 ? seq[k] : 255;
      int fb = 255;
      if (id == B_CKV + 12) fb = B_QDONE;
      else if (id >= B_DN) fb = B_ADONE;
      else if (id >= B_GU + 8) fb = B_TFREE + 3;
      else if (id >= B_GU + 3) fb = B_TFREE + 2;
      else if (id >= B_WO + 2) fb = B_TFREE + 1;
      else if (id >= B_WO) fb = B_TFREE;
      S.e[i] = make_uint2(id | (wb << 8) | (fb << 16), (unsigned)tm);
      tm += kb10[i] * pace / 2048.0;
    }
    for (int i = NSTEP; i < 64; i++) S.e[i] = make_uint2(0, 0);
  }
  fused_kernel<<<132, NTHR, SMEM_BYTES>>>(A, M, S);
}
```

```cpp
#include <cuda_runtime.h>
#include <cuda_bf16.h>
#include <cuda.h>
#include <stdint.h>

typedef __nv_bfloat16 bf16;

constexpr int PACE_T0 = 100, PACE_A = 44000, PACE_P = 43000, PACE_B = 46000, PACE_G = 46000, PACE_D = 42000;
constexpr int GAP_A = 200, GAP_B = 100, W_A = 36, W_P = 40, SW_P = 8, SKEW = 12;
constexpr int XWIN_A = 1, XWIN_P = 2, XWIN = 1, LATE_A = 800, LATE = 200, LEAK = 16, LEAK0 = 300;
constexpr int MOD2_PRE = 18, MOD2_DELAY = 6500, MOD2_STEP = 200, MOD2_GB = 2000;
constexpr int T_E1 = 1500, T_E1B = 2200, T_CLR = 1000, T_GATH = 7000;
constexpr int D_E6 = 300, TH4 = 48, NEAR_MAX = 385, PROBE_MAX = 12;
constexpr int NHARD = 3;
constexpr int NTHR = 608;
#define SPIN_LIMIT 200000
#define WAIT_UNTIL(ns) do { while ((int)(gtime32() - t0) < (ns)) ; } while (0)
#define DELAY(n) do { unsigned c0_ = clock(); while ((int)((unsigned)clock() - c0_) < (n)) ; } while (0)

constexpr int X_OFF   = 0;
constexpr int WO_OFF  = X_OFF;
constexpr int GA_OFF  = X_OFF + 36864;
constexpr int M1_OFF  = X_OFF + 98304;
constexpr int Y1_OFF  = 131072;
constexpr int SC_OFF  = Y1_OFF;
constexpr int Y2_OFF  = Y1_OFF + 36864;
constexpr int Y3_OFF  = Y2_OFF + 32768;
constexpr int DN_OFF  = Y2_OFF;
constexpr int ACT_OFF = Y3_OFF + 16384;
constexpr int ACT_P   = 1168;
constexpr int AC2_OFF = ACT_OFF + 4 * ACT_P;
constexpr int AC2_P   = 304;
constexpr int RED_OFF = AC2_OFF + 8 * AC2_P;
constexpr int SMX_OFF = RED_OFF + 4096;
constexpr int ST_OFF  = SMX_OFF + 1024;
constexpr int BAR_OFF = ST_OFF + 896;
constexpr int TAB_OFF = BAR_OFF + 640;
constexpr int SMEM_BYTES = TAB_OFF + (46 - NHARD) * 32;
static_assert(SMEM_BYTES <= 232448, "smem");
static_assert(ACT_OFF % 16 == 0 && AC2_OFF % 16 == 0 && RED_OFF % 16 == 0 && BAR_OFF % 8 == 0, "align");

constexpr int B_WQ = 0, B_WUK = 4, B_CKV = 8, B_WUV = 24, B_WO = 28, B_GU = 31, B_DN = 43;
constexpr int B_M1 = 79, B_SRECV = 56, B_GA = 60, B_GB = 61, B_DONE = 62, B_ACT = 63;
constexpr int B_PRDY = 64, B_TFREE = 68, B_QDONE = 72, B_MASK = 75, B_SC = 76, B_UVF = 77;
constexpr unsigned long long LOG2_COUNTS = 0x0031144444442222ull;
constexpr int B_EMPTY = 80;
constexpr int NSTEP = 46;

constexpr int U_PROBE = 0;
constexpr int U_MOD1  = 2;
constexpr int U_X2    = 10;
constexpr int U_Q     = 16;
constexpr int U_QA    = 80;
constexpr int U_MOD2  = 112;
constexpr int EPOCH_G = 128 * 8192;
constexpr int BLK_G   = 2 * 1024 * 1024;
constexpr size_t BOX_BYTES = (size_t)BLK_G + 128 * 65536;
__device__ __align__(256) char g_box[BOX_BYTES + 2 * 1024 * 1024];
__device__ __forceinline__ int orient(int u) { return __popc(u & 0x59) & 1; }

struct Prm { const bf16* x; const bf16* c; bf16* out; char* box; };
struct Maps { CUtensorMap wq, wuk, ckv, wuv, wo, gate80, up80, gate64, up64, down40, down32, mod2, mod1; };
struct Sched { uint2 e[64]; };

__device__ __forceinline__ uint32_t smem_u32(const void* p) { return (uint32_t)__cvta_generic_to_shared(p); }
__device__ __forceinline__ unsigned gtime32() { unsigned t; asm volatile("mov.u32 %0, %%globaltimer_lo;" : "=r"(t)); return t; }
__device__ __forceinline__ void mbar_init(uint32_t bar, int cnt) { asm volatile("mbarrier.init.shared::cta.b64 [%0], %1;" :: "r"(bar), "r"(cnt) : "memory"); }
__device__ __forceinline__ void mbar_expect_tx(uint32_t bar, uint32_t bytes) { asm volatile("mbarrier.arrive.expect_tx.shared::cta.b64 _, [%0], %1;" :: "r"(bar), "r"(bytes) : "memory"); }
__device__ __forceinline__ void mbar_arrive(uint32_t bar) { asm volatile("mbarrier.arrive.shared::cta.b64 _, [%0];" :: "r"(bar) : "memory"); }
__device__ __forceinline__ bool mbar_test(uint32_t bar, uint32_t parity) {
  uint32_t ok;
  asm volatile("{\n.reg .pred p;\nmbarrier.test_wait.parity.shared::cta.b64 p, [%1], %2;\nselp.u32 %0, 1, 0, p;\n}" : "=r"(ok) : "r"(bar), "r"(parity) : "memory");
  return ok;
}
__device__ __forceinline__ void mbar_wait(uint32_t bar, uint32_t parity) {
  asm volatile("{\n.reg .pred p, q;\n.reg .u32 n;\nmov.u32 n, 0;\n"
               "W_%=:\nmbarrier.try_wait.parity.shared::cta.b64 p, [%0], %1;\n@p bra D_%=;\n"
               "add.u32 n, n, 1;\nsetp.lt.u32 q, n, %2;\n@q bra W_%=;\nD_%=:\n}"
               :: "r"(bar), "r"(parity), "n"(SPIN_LIMIT) : "memory");
}
__device__ __forceinline__ void mbar_wait2(uint32_t b0, uint32_t b1) {
  asm volatile("{\n.reg .pred p0, p1, q;\n.reg .u32 n;\nmov.u32 n, 0;\n"
               "W_%=:\n"
               "mbarrier.try_wait.parity.shared::cta.b64 p1, [%1], 0;\n"
               "mbarrier.try_wait.parity.shared::cta.b64 p0, [%0], 0;\n"
               "and.pred p0, p0, p1;\n@p0 bra D_%=;\n"
               "add.u32 n, n, 1;\nsetp.lt.u32 q, n, %2;\n@q bra W_%=;\nD_%=:\n}"
               :: "r"(b0), "r"(b1), "n"(SPIN_LIMIT) : "memory");
}
__device__ __forceinline__ void mbar_wait4(uint32_t b0, uint32_t b1, uint32_t b2, uint32_t b3) {
  asm volatile("{\n.reg .pred p0, p1, p2, p3, q;\n.reg .u32 n;\nmov.u32 n, 0;\n"
               "W_%=:\n"
               "mbarrier.try_wait.parity.shared::cta.b64 p3, [%3], 0;\n"
               "mbarrier.try_wait.parity.shared::cta.b64 p2, [%2], 0;\n"
               "mbarrier.try_wait.parity.shared::cta.b64 p1, [%1], 0;\n"
               "mbarrier.try_wait.parity.shared::cta.b64 p0, [%0], 0;\n"
               "and.pred p0, p0, p1;\nand.pred p2, p2, p3;\nand.pred p0, p0, p2;\n@p0 bra D_%=;\n"
               "add.u32 n, n, 1;\nsetp.lt.u32 q, n, %4;\n@q bra W_%=;\nD_%=:\n}"
               :: "r"(b0), "r"(b1), "r"(b2), "r"(b3), "n"(SPIN_LIMIT) : "memory");
}
__device__ __forceinline__ bool mbar_test4(uint32_t b0, uint32_t b1, uint32_t b2, uint32_t b3) {
  uint32_t ok;
  asm volatile("{\n.reg .pred p0, p1, p2, p3;\n"
               "mbarrier.test_wait.parity.shared::cta.b64 p3, [%4], 0;\n"
               "mbarrier.test_wait.parity.shared::cta.b64 p2, [%3], 0;\n"
               "mbarrier.test_wait.parity.shared::cta.b64 p1, [%2], 0;\n"
               "mbarrier.test_wait.parity.shared::cta.b64 p0, [%1], 0;\n"
               "and.pred p0, p0, p1;\nand.pred p2, p2, p3;\nand.pred p0, p0, p2;\nselp.u32 %0, 1, 0, p0;\n}"
               : "=r"(ok) : "r"(b0), "r"(b1), "r"(b2), "r"(b3) : "memory");
  return ok;
}
__device__ __forceinline__ void tma3d(uint32_t dst, const CUtensorMap* m, int c0, int c1, int c2, uint32_t bar, uint64_t pol) {
  asm volatile("cp.async.bulk.tensor.3d.shared::cluster.global.mbarrier::complete_tx::bytes.L2::cache_hint [%0], [%1, {%3, %4, %5}], [%2], %6;"
               :: "r"(dst), "l"(m), "r"(bar), "r"(c0), "r"(c1), "r"(c2), "l"(pol) : "memory");
}
__device__ __forceinline__ void tma3d_elect(uint32_t dst, const CUtensorMap* m, int c0, int c1, int c2, uint32_t bar, uint64_t pol) {
  asm volatile("{\n.reg .pred p;\nelect.sync _|p, 0xffffffff;\n"
               "@p cp.async.bulk.tensor.3d.shared::cluster.global.mbarrier::complete_tx::bytes.L2::cache_hint [%0], [%1, {%3, %4, %5}], [%2], %6;\n}"
               :: "r"(dst), "l"(m), "r"(bar), "r"(c0), "r"(c1), "r"(c2), "l"(pol) : "memory");
}
__device__ __forceinline__ void bar_sync(int id, int n) { asm volatile("bar.sync %0, %1;" :: "r"(id), "r"(n) : "memory"); }
__device__ __forceinline__ void fence_async() { asm volatile("fence.proxy.async.shared::cta;" ::: "memory"); }
__device__ __forceinline__ uint4 ldg_rlx(const void* p) {
  unsigned long long a, b;
  asm volatile("ld.relaxed.gpu.global.v2.b64 {%0,%1}, [%2];" : "=l"(a), "=l"(b) : "l"(p) : "memory");
  return make_uint4((unsigned)a, (unsigned)(a >> 32), (unsigned)b, (unsigned)(b >> 32));
}
__device__ __forceinline__ uint4 ldg_nc(const void* p) {
  uint4 v;
  asm volatile("ld.global.nc.v4.u32 {%0,%1,%2,%3}, [%4];" : "=r"(v.x), "=r"(v.y), "=r"(v.z), "=r"(v.w) : "l"(p) : "memory");
  return v;
}
__device__ __forceinline__ uint2 ldg_rlx64(const void* p) {
  unsigned long long a;
  asm volatile("ld.relaxed.gpu.global.b64 %0, [%1];" : "=l"(a) : "l"(p) : "memory");
  return make_uint2((unsigned)a, (unsigned)(a >> 32));
}
__device__ __forceinline__ unsigned ldg_rlx32(const void* p) { unsigned v; asm volatile("ld.relaxed.gpu.global.u32 %0, [%1];" : "=r"(v) : "l"(p) : "memory"); return v; }
__device__ __forceinline__ void stg_rlx(void* p, uint4 v) {
  unsigned long long a = ((unsigned long long)v.y << 32) | v.x, b = ((unsigned long long)v.w << 32) | v.z;
  asm volatile("st.relaxed.gpu.global.v2.b64 [%0], {%1,%2};" :: "l"(p), "l"(a), "l"(b) : "memory");
}
__device__ __forceinline__ void stg_rlx64(void* p, unsigned x, unsigned y) {
  unsigned long long a = ((unsigned long long)y << 32) | x;
  asm volatile("st.relaxed.gpu.global.b64 [%0], %1;" :: "l"(p), "l"(a) : "memory");
}
__device__ __forceinline__ void stg_rlx64_if(bool c, void* p, unsigned x, unsigned y) {
  unsigned long long a = ((unsigned long long)y << 32) | x;
  asm volatile("{\n.reg .pred p;\nsetp.ne.u32 p, %2, 0;\n@p st.relaxed.gpu.global.b64 [%0], %1;\n}" :: "l"(p), "l"(a), "r"((unsigned)c) : "memory");
}
__device__ __forceinline__ void ldg_rlx_if(bool c, const void* p, uint4& v) {
  unsigned long long a = ((unsigned long long)v.y << 32) | v.x, b = ((unsigned long long)v.w << 32) | v.z;
  asm volatile("{\n.reg .pred p;\nsetp.ne.u32 p, %3, 0;\n@p ld.relaxed.gpu.global.v2.b64 {%0,%1}, [%2];\n}" : "+l"(a), "+l"(b) : "l"(p), "r"((unsigned)c) : "memory");
  v = make_uint4((unsigned)a, (unsigned)(a >> 32), (unsigned)b, (unsigned)(b >> 32));
}
__device__ __forceinline__ void stg_rlx32(void* p, unsigned x) { asm volatile("st.relaxed.gpu.global.u32 [%0], %1;" :: "l"(p), "r"(x) : "memory"); }
__device__ __forceinline__ uint32_t lds32(uint32_t a) { uint32_t v; asm volatile("ld.shared.u32 %0, [%1];" : "=r"(v) : "r"(a) : "memory"); return v; }
__device__ __forceinline__ uint32_t lds32v(uint32_t a) { uint32_t v; asm volatile("ld.volatile.shared.u32 %0, [%1];" : "=r"(v) : "r"(a) : "memory"); return v; }
__device__ __forceinline__ float lds32f(uint32_t a) { float v; asm volatile("ld.shared.f32 %0, [%1];" : "=f"(v) : "r"(a) : "memory"); return v; }
__device__ __forceinline__ uint2 lds64(uint32_t a) { uint2 v; asm volatile("ld.shared.v2.u32 {%0,%1}, [%2];" : "=r"(v.x), "=r"(v.y) : "r"(a) : "memory"); return v; }
__device__ __forceinline__ uint4 lds128(uint32_t a) { uint4 v; asm volatile("ld.shared.v4.u32 {%0,%1,%2,%3}, [%4];" : "=r"(v.x), "=r"(v.y), "=r"(v.z), "=r"(v.w) : "r"(a) : "memory"); return v; }
__device__ __forceinline__ void sts16(uint32_t a, uint16_t v) { asm volatile("st.shared.u16 [%0], %1;" :: "r"(a), "h"(v) : "memory"); }
__device__ __forceinline__ void sts32(uint32_t a, uint32_t v) { asm volatile("st.shared.u32 [%0], %1;" :: "r"(a), "r"(v) : "memory"); }
__device__ __forceinline__ void sts32f(uint32_t a, float v) { asm volatile("st.shared.f32 [%0], %1;" :: "r"(a), "f"(v) : "memory"); }
__device__ __forceinline__ void sts64f(uint32_t a, float x, float y) { asm volatile("st.shared.v2.f32 [%0], {%1,%2};" :: "r"(a), "f"(x), "f"(y) : "memory"); }
__device__ __forceinline__ void sts128(uint32_t a, uint4 v) { asm volatile("st.shared.v4.u32 [%0], {%1,%2,%3,%4};" :: "r"(a), "r"(v.x), "r"(v.y), "r"(v.z), "r"(v.w) : "memory"); }
__device__ __forceinline__ void ldsm4t(uint32_t (&r)[4], uint32_t a) {
  asm volatile("ldmatrix.sync.aligned.m8n8.x4.trans.shared.b16 {%0,%1,%2,%3}, [%4];" : "=r"(r[0]), "=r"(r[1]), "=r"(r[2]), "=r"(r[3]) : "r"(a) : "memory");
}
__device__ __forceinline__ void ldsm4(uint32_t (&r)[4], uint32_t a) {
  asm volatile("ldmatrix.sync.aligned.m8n8.x4.shared.b16 {%0,%1,%2,%3}, [%4];" : "=r"(r[0]), "=r"(r[1]), "=r"(r[2]), "=r"(r[3]) : "r"(a) : "memory");
}
__device__ __forceinline__ void ldsm2t(uint32_t (&r)[2], uint32_t a) {
  asm volatile("ldmatrix.sync.aligned.m8n8.x2.trans.shared.b16 {%0,%1}, [%2];" : "=r"(r[0]), "=r"(r[1]) : "r"(a) : "memory");
}
__device__ __forceinline__ void mma16(float (&d)[4], const uint32_t (&a)[4], uint32_t b0, uint32_t b1) {
  asm volatile("mma.sync.aligned.m16n8k16.row.col.f32.bf16.bf16.f32 {%0,%1,%2,%3}, {%4,%5,%6,%7}, {%8,%9}, {%0,%1,%2,%3};"
               : "+f"(d[0]), "+f"(d[1]), "+f"(d[2]), "+f"(d[3]) : "r"(a[0]), "r"(a[1]), "r"(a[2]), "r"(a[3]), "r"(b0), "r"(b1));
}
__device__ __forceinline__ void mma8(float (&d)[4], const uint32_t (&a)[2], uint32_t b0) {
  asm volatile("mma.sync.aligned.m16n8k8.row.col.f32.bf16.bf16.f32 {%0,%1,%2,%3}, {%4,%5}, {%6}, {%0,%1,%2,%3};"
               : "+f"(d[0]), "+f"(d[1]), "+f"(d[2]), "+f"(d[3]) : "r"(a[0]), "r"(a[1]), "r"(b0));
}
__device__ __forceinline__ uint32_t pack_bf16(float lo, float hi) { uint32_t r; asm("cvt.rn.bf16x2.f32 %0, %1, %2;" : "=r"(r) : "f"(hi), "f"(lo)); return r; }
__device__ __forceinline__ uint16_t to_bf16(float v) { return (uint16_t)(pack_bf16(v, 0.f) & 0xFFFFu); }
__device__ __forceinline__ float bf_lo(uint32_t v) { return __uint_as_float(v << 16); }
__device__ __forceinline__ float bf_hi(uint32_t v) { return __uint_as_float(v & 0xFFFF0000u); }
__device__ __forceinline__ float ex2(float x) { float r; asm("ex2.approx.ftz.f32 %0, %1;" : "=f"(r) : "f"(x)); return r; }
__device__ __forceinline__ float silu(float v) { return __fdividef(v, 1.f + __expf(-v)); }
__device__ __forceinline__ unsigned tagf(float v, unsigned par) { return (__float_as_uint(v) & ~1u) | par; }
__device__ __forceinline__ unsigned tagb(unsigned w, unsigned par) { return ((w + ((w >> 1) & 1u)) & ~1u) | par; }
__device__ __forceinline__ bool ok4(const uint4& v, unsigned par) { return ((((v.x ^ par) | (v.y ^ par) | (v.z ^ par) | (v.w ^ par)) & 1u) == 0); }
__device__ __forceinline__ bool ok2(const uint4& v, unsigned par) { return ((((v.x ^ par) | (v.z ^ par)) & 1u) == 0); }
__device__ __forceinline__ int fkey(float f) { int b = __float_as_int(f); return b ^ ((b >> 31) & 0x7FFFFFFF); }
__device__ __forceinline__ float funkey(int k) { return __int_as_float(k ^ ((k >> 31) & 0x7FFFFFFF)); }

template <int TA, int TB>
__device__ __forceinline__ void wgmma_n32(float (&d)[16], uint64_t da, uint64_t db, int accum) {
  asm volatile("{\n.reg .pred p;\nsetp.ne.b32 p, %18, 0;\n"
               "wgmma.mma_async.sync.aligned.m64n32k16.f32.bf16.bf16 {%0,%1,%2,%3,%4,%5,%6,%7,%8,%9,%10,%11,%12,%13,%14,%15}, %16, %17, p, 1, 1, %19, %20;\n}"
               : "+f"(d[0]), "+f"(d[1]), "+f"(d[2]), "+f"(d[3]), "+f"(d[4]), "+f"(d[5]), "+f"(d[6]), "+f"(d[7]),
                 "+f"(d[8]), "+f"(d[9]), "+f"(d[10]), "+f"(d[11]), "+f"(d[12]), "+f"(d[13]), "+f"(d[14]), "+f"(d[15])
               : "l"(da), "l"(db), "r"(accum), "n"(TA), "n"(TB) : "memory");
}
__device__ __forceinline__ void wg_fence() { asm volatile("wgmma.fence.sync.aligned;" ::: "memory"); }
__device__ __forceinline__ void wg_commit() { asm volatile("wgmma.commit_group.sync.aligned;" ::: "memory"); }
__device__ __forceinline__ void wg_wait0() { asm volatile("wgmma.wait_group.sync.aligned 0;" ::: "memory"); }
__device__ __forceinline__ uint64_t mkdesc(uint32_t addr, uint32_t sbo, uint32_t swz) {
  return (uint64_t)((addr & 0x3FFFF) >> 4) | ((uint64_t)1 << 16) | ((uint64_t)(sbo >> 4) << 32) | ((uint64_t)swz << 62);
}

__device__ __forceinline__ void poll_fin(const void* p, unsigned par, uint4& v) {
#pragma unroll 1
  for (int it = 0; it < SPIN_LIMIT; it++) {
    const bool bad = !ok2(v, par);
    if (!__any_sync(0xffffffffu, bad)) break;
    ldg_rlx_if(bad, p, v);
  }
}
__device__ __forceinline__ void poll_fin2(const void* p0, const void* p1, unsigned par, uint4& v0, uint4& v1) {
#pragma unroll 1
  for (int it = 0; it < SPIN_LIMIT; it++) {
    const bool b0 = !ok2(v0, par), b1 = !ok2(v1, par);
    if (!__any_sync(0xffffffffu, b0 || b1)) break;
    ldg_rlx_if(b0, p0, v0);
    ldg_rlx_if(b1, p1, v1);
  }
}
__device__ __forceinline__ uint4 poll16(const void* p, unsigned par) { uint4 v = ldg_rlx(p); poll_fin(p, par, v); return v; }
__device__ __forceinline__ void poll16x2(const void* p0, const void* p1, unsigned par, uint4& v0, uint4& v1) {
  v0 = ldg_rlx(p0); v1 = ldg_rlx(p1); poll_fin2(p0, p1, par, v0, v1);
}
__device__ __forceinline__ void poll32_fin(const void* p, unsigned par, unsigned& v) {
#pragma unroll 1
  for (int it = 0; it < SPIN_LIMIT; it++) {
    const bool bad = (v ^ par) & 1u;
    if (!__any_sync(0xffffffffu, bad)) break;
    DELAY(150);
    if (bad) v = ldg_rlx32(p);
  }
}
#define NEAR(u) (G + (u) * 8192 + ((orient(u) ^ p0) << 12))
#define PIN(x) x = __shfl_sync(0xffffffffu, x, lane)
#define KEEP(x) asm volatile("" : "+r"(x))
#define KEEPL(x) asm volatile("" : "+l"(x))

template <int B1, int B0>
__device__ __forceinline__ float xreduce4(float s0, float s1, float s2, float s3, int lane) {
  const bool hi = lane & B1, lo = lane & B0;
  float a = hi ? s0 : s2, b = hi ? s1 : s3;
  a = __shfl_xor_sync(0xffffffffu, a, B1); b = __shfl_xor_sync(0xffffffffu, b, B1);
  s0 = (hi ? s2 : s0) + a; s1 = (hi ? s3 : s1) + b;
  float c = lo ? s0 : s1;
  c = __shfl_xor_sync(0xffffffffu, c, B0);
  return (lo ? s1 : s0) + c;
}
template <bool MAX>
__device__ __forceinline__ float xreduce8(const float (&a)[8], int lane) {
  const bool b4 = lane & 16, b3 = lane & 8, b2 = lane & 4;
  float u[4], w[2];
#pragma unroll
  for (int e = 0; e < 4; e++) { float snd = b4 ? a[e] : a[4 + e], keep = b4 ? a[4 + e] : a[e]; snd = __shfl_xor_sync(0xffffffffu, snd, 16); u[e] = MAX ? fmaxf(keep, snd) : keep + snd; }
#pragma unroll
  for (int e = 0; e < 2; e++) { float snd = b3 ? u[e] : u[2 + e], keep = b3 ? u[2 + e] : u[e]; snd = __shfl_xor_sync(0xffffffffu, snd, 8); w[e] = MAX ? fmaxf(keep, snd) : keep + snd; }
  float snd = b2 ? w[0] : w[1], keep = b2 ? w[1] : w[0];
  snd = __shfl_xor_sync(0xffffffffu, snd, 4);
  return MAX ? fmaxf(keep, snd) : keep + snd;
}
#define UF(x) __uint_as_float(x)

template <class F>
__device__ __forceinline__ void reduce_pieces(const char* src, unsigned tag, uint32_t sb, int warp, int lane, uint32_t gbar, uint32_t xa, uint32_t ga, F fin) {
  const int g = lane >> 2, t = lane & 3;
  uint32_t sa = sb + RED_OFF + (t * 8 + g) * 80 + warp * 4;
  KEEP(sa);
  uint4 v = poll16(src, tag);
  v.x &= ~1u; v.z &= ~1u;
  const float a[8] = {bf_lo(v.x), bf_hi(v.x), bf_lo(v.y), bf_hi(v.y), bf_lo(v.z), bf_hi(v.z), bf_lo(v.w), bf_hi(v.w)};
  sts32f(sa, xreduce8<false>(a, lane));
  if (warp == 0) {
    mbar_wait(gbar, 0);
    const float x = lds32f(xa + lane * 4), gt = lds32f(ga + lane * 4);
    bar_sync(3, 512);
    uint4 w[4];
#pragma unroll
    for (int q = 0; q < 4; q++) w[q] = lds128(sb + RED_OFF + lane * 80 + q * 16);
    float r[4];
#pragma unroll
    for (int q = 0; q < 4; q++) r[q] = (UF(w[q].x) + UF(w[q].y)) + (UF(w[q].z) + UF(w[q].w));
    fin(x + gt * ((r[0] + r[1]) + (r[2] + r[3])));
  } else {
    asm volatile("bar.arrive 3, 512;" ::: "memory");
  }
}
__device__ __forceinline__ void send_pieces(char* G, const uint32_t (&off)[3], const float (&d)[3][4], int t, unsigned tag) {
  uint32_t w0[3], w1[3], o[3];
#pragma unroll
  for (int m = 0; m < 3; m++) {
    w0[m] = pack_bf16(d[m][0], d[m][1]); w1[m] = pack_bf16(d[m][2], d[m][3]);
    o[m] = __shfl_xor_sync(0xffffffffu, (t & 1) ? w0[m] : w1[m], 1);
  }
#pragma unroll
  for (int m = 0; m < 3; m++) stg_rlx64_if(t < 2, G + off[m], tagb((t & 1) ? o[m] : w0[m], tag), (t & 1) ? w1[m] : o[m]);
}
__device__ __forceinline__ uint32_t hsel(uint32_t sb, int c) { return (lds32(sb + ST_OFF + 80 + (c >> 5) * 4) >> (c & 31)) & 1u; }

__global__ void __cluster_dims__(2, 1, 1) __launch_bounds__(NTHR, 1)
fused_kernel(const __grid_constant__ Prm A, const __grid_constant__ Maps M, const __grid_constant__ Sched S) {
  extern __shared__ __align__(1024) char sm[];
  const int tid = threadIdx.x, tz = __shfl_sync(0xffffffffu, (int)threadIdx.x, threadIdx.x & 31) - tid, cta = __shfl_sync(0xffffffffu, (int)blockIdx.x, 0);
  const int warp = __shfl_sync(0xffffffffu, tid >> 5, 0), lane = tid & 31, g = lane >> 2, t = lane & 3;
  const uint32_t sb = __shfl_sync(0xffffffffu, smem_u32(sm), 0);
  const uint32_t bars = sb + BAR_OFF;
  const unsigned t0 = gtime32();

  uint64_t pol = 0;
  if (warp == 16) {
    if (lane == 0) {
#pragma unroll
      for (int k = 0; k < NHARD; k++) mbar_init(bars + 8 * k, 1);
      mbar_init(bars + 8 * B_M1, 1);
      asm volatile("fence.mbarrier_init.release.cluster;" ::: "memory");
      if (cta < 128) {
#pragma unroll
        for (int k = 0; k < NHARD; k++) mbar_expect_tx(bars + 8 * k, 9216);
        mbar_expect_tx(bars + 8 * B_M1, 12288);
      }
    }
    __syncwarp();
    asm volatile("createpolicy.fractional.L2::evict_first.b64 %0, 1.0;" : "=l"(pol));
    if (cta < 108) tma3d_elect(sb + M1_OFF, &M.mod1, (cta % 36) * 32, (cta / 36) * 192, 0, bars + 8 * B_M1, pol);
    if (cta < 128) tma3d_elect(sb + Y1_OFF, &M.wq, 0, (cta & 3) * 144, (cta >> 2) * 2, bars, pol);
  }
  unsigned par = 0;
  uint4 cx = make_uint4(0, 0, 0, 0);
  uint4 xx = make_uint4(0, 0, 0, 0);
  if (warp < 16) {
    if (tid < 288) {
      if (cta < 108 || cta >= 128) cx = ldg_nc((const uint4*)A.c + tid);
      xx = ldg_nc((const uint4*)A.x + tid);
    }
    par = ldg_rlx32(A.box + EPOCH_G + tz);
    if (lane == 0) {
#pragma unroll
      for (int k = 0; k < 4; k++) if (k || warp >= NHARD) mbar_init(bars + 8 * (warp + 16 * k), 1);
      if (warp != 15) mbar_init(bars + 8 * (warp + 64), 1 << ((int)(LOG2_COUNTS >> (4 * warp)) & 15));
      if ((warp >> 2) == 2) mbar_expect_tx(bars + 8 * (warp + 48), 8192);
      if (warp == 15) mbar_expect_tx(bars + 8 * B_ACT, (cta & 8) ? 3840 : 3072);
      asm volatile("fence.mbarrier_init.release.cluster;" ::: "memory");
    }
    __syncwarp();
    if (tid < 128) sts32(sb + SMX_OFF + tid * 4, 0x80000000u);
  }
  if (warp == 17 || warp == 18) {
    const int hf = warp - 17;
    char* p0a = A.box + U_PROBE * 8192 + (cta & 127) * 32 + hf * 4096;
    char* p1a = A.box + BLK_G + (cta & 127) * 65536 + hf * 4096;
    if (lane < 4 && cta < 128) stg_rlx((lane < 2 ? p0a : p1a) + (lane & 1) * 16, make_uint4(0, 0, 0, 0));
    if (lane == 0) sts32(sb + ST_OFF + 64 + hf * 4, 0);
    bar_sync(8, 64);
    asm volatile("bar.arrive 0, %0;" :: "n"(NTHR) : "memory");
    if (lane == 0 && cta < 128) {
#pragma unroll 1
      for (int k = 0; k < 2; k++) {
        unsigned best = 0xffffffffu;
#pragma unroll 1
        for (int r = 0; r < PROBE_MAX; r++) {
          unsigned v;
          const unsigned cs = clock();
          asm volatile("atom.relaxed.gpu.global.exch.b32 %0, [%1], 0;" : "=r"(v) : "l"(k ? p1a : p0a) : "memory");
          if (v == 0) best = min(best, (unsigned)clock() - cs);
          if (best < (unsigned)NEAR_MAX) sts32(sb + ST_OFF + 64 + k * 4, 2u | hf);
          if (lds32v(sb + ST_OFF + 64 + k * 4)) break;
        }
        sts32(sb + ST_OFF + 72 + hf * 4, best);
      }
    }
    __syncwarp();
    bar_sync(10, 96);
  } else if (warp == 16) {
    asm volatile("bar.arrive 0, %0;" :: "n"(NTHR) : "memory");
  } else {
    bar_sync(0, NTHR);
    if (warp == 15) asm volatile("bar.arrive 10, 96;" ::: "memory");
    if (warp == 14) asm volatile("bar.arrive 11, 64;" ::: "memory");
  }

  if (warp > 16) {
    if (cta >= 128) return;
    asm volatile("barrier.cluster.arrive.relaxed.aligned;" ::: "memory");
    char* const G = A.box;
    const int hf = warp - 17, ht = tid - 544;
    char* const blk = G + BLK_G + cta * 65536;
    const unsigned epoch = ldg_rlx32(G + EPOCH_G + tz) + 1u;
    bar_sync(8, 64);
    unsigned hb = lds32(sb + ST_OFF + 68);
    { const uint2 lt = lds64(sb + ST_OFF + 72); hb = hb ? hb & 1u : (lt.x > lt.y ? 1u : 0u); }
    WAIT_UNTIL(T_CLR);
#pragma unroll 1
    for (int u = 0; u < 7; u++) {
      if (cta >= 72 && (u == 1 || u == 3)) continue;
      char* pa = blk + u * 8192 + ((hb ^ (u & 1)) << 12) + ht * 16;
#pragma unroll
      for (int q = 0; q < 4; q++) stg_rlx(pa + q * 1024, make_uint4(0, 0, 0, 0));
    }
    bar_sync(8, 64);
    if (ht == 0) { __threadfence(); stg_rlx32(blk + 7 * 8192, (epoch << 1) | hb); }
    WAIT_UNTIL(T_GATH);
    {
      const char* pa = G + BLK_G + ht * 65536 + 7 * 8192;
      const unsigned want = epoch & 0x7fffffffu;
      unsigned v0 = ldg_rlx32(pa), v1 = ldg_rlx32(pa + 64 * 65536);
#pragma unroll 1
      for (int it = 0; it < SPIN_LIMIT; it++) {
        const bool b0 = (v0 >> 1) != want, b1 = (v1 >> 1) != want;
        if (!__any_sync(0xffffffffu, b0 || b1)) break;
        DELAY(200);
        if (b0) v0 = ldg_rlx32(pa);
        if (b1) v1 = ldg_rlx32(pa + 64 * 65536);
      }
      const unsigned m0 = __ballot_sync(0xffffffffu, v0 & 1u), m1 = __ballot_sync(0xffffffffu, v1 & 1u);
      if (lane == 0) { sts32(sb + ST_OFF + 80 + hf * 4, m0); sts32(sb + ST_OFF + 88 + hf * 4, m1); }
    }
    if (lane == 0) mbar_arrive(bars + 8 * B_MASK);
    bar_sync(8, 64);
    if (hf == 1) {
      const int g = lane >> 2, t = lane & 3, hd = (lane & 24) + 2 * t + (g & 1);
      const int c0 = hd * 4 + (cta & 1) * 2;
      char* m0 = G + BLK_G + c0 * 65536 + 5 * 8192 + ((hsel(sb, c0) ^ 1u) << 12) + 2048 + (cta >> 1) * 32;
      char* m1 = G + BLK_G + (c0 + 1) * 65536 + 5 * 8192 + ((hsel(sb, c0 + 1) ^ 1u) << 12) + 2048 + (cta >> 1) * 32;
      const uint32_t ones[4] = {0x3F803F80u, 0x3F803F80u, 0x3F803F80u, 0x3F803F80u};
      const uint32_t pa = sb + Y2_OFF + (lane & 15) * 64 + (((lane >> 4) ^ ((lane >> 1) & 3)) << 4);
      float l = 0.f;
#pragma unroll 1
      for (int i = 0; i < 4; i++) {
        mbar_wait(bars + 8 * (B_PRDY + i), 0);
        float d[4][4] = {{0, 0, 0, 0}, {0, 0, 0, 0}, {0, 0, 0, 0}, {0, 0, 0, 0}};
        uint32_t b[8][4];
#pragma unroll
        for (int ks = 0; ks < 4; ks++) { ldsm4t(b[2 * ks], pa + i * 8192 + ks * 1024); ldsm4t(b[2 * ks + 1], (pa ^ 32) + i * 8192 + ks * 1024); }
        const float f = lds32f(sb + SMX_OFF + 512 + (i * 32 + hd) * 4);
#pragma unroll
        for (int ks = 0; ks < 4; ks++) {
          mma16(d[0], ones, b[2 * ks][0], b[2 * ks][1]); mma16(d[1], ones, b[2 * ks][2], b[2 * ks][3]);
          mma16(d[2], ones, b[2 * ks + 1][0], b[2 * ks + 1][1]); mma16(d[3], ones, b[2 * ks + 1][2], b[2 * ks + 1][3]);
        }
        const float e0 = (g & 1) ? d[0][1] : d[0][0], e1 = (g & 1) ? d[1][1] : d[1][0], e2 = (g & 1) ? d[2][1] : d[2][0], e3 = (g & 1) ? d[3][1] : d[3][0];
        l = l * f + ((g & 4) ? ((g & 2) ? e3 : e2) : ((g & 2) ? e1 : e0));
      }
      const float mm = funkey((int)lds32(sb + SMX_OFF + (96 + hd) * 4));
      stg_rlx64(m0, tagf(l, 1u), __float_as_uint(mm));
      stg_rlx64(m1, tagf(l, 1u), __float_as_uint(mm));
    }
    {
      const unsigned par = epoch & 1u;
      const int p0 = (int)lds32v(sb + ST_OFF + 64) & 1;
      if (hf == 0 && cta < 72) {
        const char* pa = NEAR(U_MOD2 + cta / 18) + ((cta % 18) * 32 + lane) * 4;
        unsigned v = ldg_rlx32(pa);
        poll32_fin(pa, par, v);
        sts32(sb + ST_OFF + 512 + lane * 4, v);
        __syncwarp();
        if (lane == 0) mbar_arrive(bars + 8 * B_GA);
      }
      uint32_t pk[2][9][2];
#pragma unroll
      for (int k = 0; k < 2; k++) {
        const char* pa = NEAR(U_MOD2 + (k + 1) * 4 + (ht >> 4)) + (ht & 15) * 16;
        { unsigned v = ldg_rlx32(pa); poll32_fin(pa, par, v); }
#pragma unroll 1
        for (int it = 0; it < SPIN_LIMIT; it++) {
          uint4 a[9];
#pragma unroll
          for (int e = 0; e < 9; e++) a[e] = ldg_rlx(pa + e * 256);
          bool ok = true;
#pragma unroll
          for (int e = 0; e < 9; e++) {
            ok = ok && ok4(a[e], par);
            pk[k][e][0] = pack_bf16(UF(a[e].x), UF(a[e].y)); pk[k][e][1] = pack_bf16(UF(a[e].z), UF(a[e].w));
          }
          if (__all_sync(0xffffffffu, ok)) break;
        }
      }
      mbar_wait(bars + 8 * B_UVF, 0);
#pragma unroll
      for (int e = 0; e < 9; e++) sts128(sb + SC_OFF + ((ht >> 4) * 144 + (ht & 15) + e * 16) * 16, make_uint4(pk[0][e][0], pk[0][e][1], pk[1][e][0], pk[1][e][1]));
      __syncwarp();
      if (lane == 0) mbar_arrive(bars + 8 * B_SC);
      if (hf == 0 && cta < 72) {
        const char* pa = NEAR(U_MOD2 + 12 + cta / 18) + ((cta % 18) * 32 + lane) * 4;
        unsigned v = ldg_rlx32(pa);
        poll32_fin(pa, par, v);
        sts32(sb + ST_OFF + 640 + lane * 4, v);
        __syncwarp();
        if (lane == 0) mbar_arrive(bars + 8 * B_GB);
      }
    }
    __syncwarp();
    asm volatile("barrier.cluster.wait.aligned;" ::: "memory");
    return;
  }
  if (warp == 16) {
    if (cta < 128) asm volatile("barrier.cluster.arrive.relaxed.aligned;" ::: "memory");
    if (cta < 128) {
      const int h = cta >> 2, j = cta & 3;
      uint2 se0 = S.e[lane], se1 = S.e[32 + lane];
      PIN(se0.x); PIN(se0.y); PIN(se1.x); PIN(se1.y);
#pragma unroll
      for (int c = 1; c < NHARD; c++) {
        WAIT_UNTIL(PACE_T0 + c * (9 * PACE_A >> 10));
        tma3d_elect(sb + Y1_OFF + (c & 1) * 18432 + (c >> 1) * 9216, &M.wq, 0, j * 144 + (c >> 1) * 72, h * 2 + (c & 1), bars + 8 * c, pol);
      }
      bar_sync(11, 64);
      if (lane == 0) mbar_arrive(bars + 8 * B_DONE);
      int nst = 0;
      const bool wide = cta & 8;
      const int fcol = (cta >> 4) * 576 + (wide ? 256 + ((cta >> 1) & 3) * 80 : ((cta >> 1) & 3) * 64);
#pragma unroll 1
      for (int q = 0; q < 2; q++) {
        const uint32_t x = q ? se1.x : se0.x;
        const int id = x & 255, wb = (x >> 8) & 255, fb = (x >> 16) & 255, wl = x >> 24;
        int map, c0 = 0, c1, c2, dst, b256;
        if (id < B_CKV || (id >= B_WUV && id < B_WO)) {
          const int c = id & 3, wq_ = id < B_WUK;
          map = wq_ ? 0 : (id < B_CKV ? 1 : 3);
          c2 = h * 2 + (c & 1);
          c1 = wq_ ? j * 144 + (c >> 1) * 72 : j * 128 + (c >> 1) * 64;
          dst = (map == 1 ? Y2_OFF : Y1_OFF) + (wq_ ? (c & 1) * 18432 + (c >> 1) * 9216 : (c & 1) * 16384 + (c >> 1) * 8192);
          b256 = wq_ ? 36 : 32;
        } else if (id < B_WUV) {
          const int c = id - B_CKV;
          map = 2; c2 = (cta & 1) * 4 + (c & 3); c1 = (cta >> 1) * 256 + (c >> 2) * 64; dst = X_OFF + c * 8192; b256 = 32;
        } else if (id < B_GU) {
          const int c = id - B_WO;
          map = 4; c2 = c * 3; c1 = cta * 32; dst = WO_OFF + c * 12288; b256 = 48;
        } else if (id < B_DN) {
          const int c = id - B_GU;
          map = (wide ? 5 : 7) + (cta & 1); c0 = fcol; c2 = 0; c1 = c * 48; b256 = wide ? 30 : 24; dst = GA_OFF + c * (b256 << 8);
        } else {
          const int c = id - B_DN;
          map = wide ? 9 : 10; c2 = c * 3; c1 = fcol + (cta & 1) * (wide ? 40 : 32); b256 = wide ? 60 : 48; dst = DN_OFF + c * (b256 << 8);
        }
        const uint32_t bar = bars + 8 * id, wbar = bars + 8 * (wl != 255 ? wl : B_DONE), fbar = bars + 8 * (fb != 255 ? fb : B_DONE);
        const int step = q * 32 + lane;
        const bool use = step >= NHARD && step < NSTEP;
        const unsigned um = __ballot_sync(0xffffffffu, use);
        if (use) {
          const uint32_t ta = sb + TAB_OFF + (nst + __popc(um & ((1u << lane) - 1u))) * 32;
          sts128(ta, make_uint4(sb + dst, bar, c0 | (c2 << 16), c1 | ((wb != 255 ? wb : B_DONE) << 19)));
          sts128(ta + 16, make_uint4(wbar, fbar, t0 + (((q ? se1.y : se0.y) >> ((cta >> 6) * 16)) & 0xFFFF), (b256 << 8) | (map << 23)));
        }
        nst += __popc(um);
      }
      __syncwarp();
      {
        int shift = 0;
#pragma unroll 1
        for (int n = 0; n < NSTEP - NHARD; n++) {
          const uint4 ea = lds128(sb + TAB_OFF + n * 32), eb = lds128(sb + TAB_OFF + n * 32 + 16);
          const uint32_t u_dst = __shfl_sync(0xffffffffu, ea.x, 0), u_bar = __shfl_sync(0xffffffffu, ea.y, 0);
          const uint32_t u_c = __shfl_sync(0xffffffffu, ea.z, 0), u_c1 = __shfl_sync(0xffffffffu, ea.w, 0) & 0xFFFF;
          const CUtensorMap* mp = (const CUtensorMap*)((const char*)&M.wq + (__shfl_sync(0xffffffffu, eb.w, 0) >> 16));
          if (lane == 0) mbar_expect_tx(ea.y, eb.w & 0xFFFF);
          int late;
          asm volatile("{\n.reg .pred pf, pw, pl, q;\n.reg .u32 n, t;\nmov.u32 n, 0;\n"
                       "W_%=:\n"
                       "mov.u32 t, %%globaltimer_lo;\n"
                       "mbarrier.test_wait.parity.shared::cta.b64 pw, [%1], 0;\n"
                       "mbarrier.test_wait.parity.shared::cta.b64 pl, [%2], 0;\n"
                       "mbarrier.test_wait.parity.shared::cta.b64 pf, [%3], 0;\n"
                       "sub.u32 t, t, %4;\n"
                       "setp.ge.and.s32 pw, t, 0, pw;\n"
                       "setp.ge.and.s32 pl, t, %5, pl;\n"
                       "or.pred pw, pw, pl;\nand.pred pw, pw, pf;\n@pw bra.uni D_%=;\n"
                       "add.u32 n, n, 1;\nsetp.lt.u32 q, n, %6;\n@q bra.uni W_%=;\nD_%=:\nmov.u32 %0, t;\n}"
                       : "=r"(late) : "r"(bars + (ea.w >> 16)), "r"(eb.x), "r"(eb.y), "r"(eb.z + shift), "r"(n < B_CKV + SW_P - NHARD ? LATE_A : LATE), "n"(4 * SPIN_LIMIT) : "memory");
          tma3d_elect(u_dst, mp, u_c & 0xFFFF, u_c1, u_c >> 16, u_bar, pol);
          shift += (max(late - LEAK0, 0) * LEAK) >> 8;
        }
      }
    } else {
      bar_sync(11, 64);
      if (lane == 0) {
#pragma unroll 1
        for (int k = 0; k < 11; k++) mbar_init(bars + 8 * (B_EMPTY + k), 9);
        const int q = cta - 128;
        int slot = 0, ph = 0, grp = 0, kc = 0;
#pragma unroll 1
        for (int n = 0; n < 36; n++) {
          if (n >= 11) mbar_wait(bars + 8 * (B_EMPTY + slot), ph ^ 1);
          if (n >= MOD2_PRE) WAIT_UNTIL(MOD2_DELAY + n * MOD2_STEP + (n >= 27 ? MOD2_GB : 0));
          mbar_expect_tx(bars + 8 * slot, 18432);
          tma3d(sb + slot * 18432, &M.mod2, 1152 + grp * 576 + q * 144, kc * 64, 0, bars + 8 * slot, pol);
          if (++slot == 11) { slot = 0; ph ^= 1; }
          if (++kc == 9) { kc = 0; grp++; }
        }
      }
    }
    __syncwarp();
    if (cta < 128) asm volatile("barrier.cluster.wait.aligned;" ::: "memory");
    return;
  }

  char* const G = A.box;

  if ((cta < 108 || cta >= 128) && tid < 288) {
    int b = tid / 72, k = (tid % 72) * 8;
    uint4 o;
    o.x = pack_bf16(silu(bf_lo(cx.x)), silu(bf_hi(cx.x))); o.y = pack_bf16(silu(bf_lo(cx.y)), silu(bf_hi(cx.y)));
    o.z = pack_bf16(silu(bf_lo(cx.z)), silu(bf_hi(cx.z))); o.w = pack_bf16(silu(bf_lo(cx.w)), silu(bf_hi(cx.w)));
    sts128(sb + ACT_OFF + b * ACT_P + k * 2, o);
  }
  KEEP(par);
  par = (par + 1u) & 1u;

  if (cta >= 128) {
    bar_sync(1, 512);
    if (warp < 9) {
      const int q = cta - 128;
      int slot = 0, ph = 0;
      const uint32_t aoff = ((lane >> 4) * 8 + (lane & 7)) * 288 + (warp * 16 + ((lane >> 3) & 1) * 8) * 2;
      const uint32_t boff = sb + ACT_OFF + (lane & 3) * ACT_P + (lane >> 3) * 16;
#pragma unroll 1
      for (int grp = 0; grp < 4; grp++) {
        float d0[4] = {0, 0, 0, 0}, d1[4] = {0, 0, 0, 0};
#pragma unroll 1
        for (int kc = 0; kc < 9; kc++) {
          mbar_wait(bars + 8 * slot, ph);
          uint32_t a[4][4], b[2][4];
#pragma unroll
          for (int e = 0; e < 4; e++) ldsm4t(a[e], sb + slot * 18432 + aoff + e * 16 * 288);
          ldsm4(b[0], boff + kc * 128); ldsm4(b[1], boff + kc * 128 + 64);
          mma16(d0, a[0], b[0][0], b[0][1]); mma16(d1, a[1], b[0][2], b[0][3]);
          mma16(d0, a[2], b[1][0], b[1][1]); mma16(d1, a[3], b[1][2], b[1][3]);
          __syncwarp();
          if (lane == 0) mbar_arrive(bars + 8 * (B_EMPTY + slot));
          if (++slot == 11) { slot = 0; ph ^= 1; }
        }
        char* dst = G + (U_MOD2 + grp * 4 + q) * 8192 + (t >> 1) * 4096 + (warp * 16 + g) * 16 + (t & 1) * 8;
        stg_rlx64(dst, tagf(d0[0] + d1[0], par), tagf(d0[1] + d1[1], par));
        stg_rlx64(dst + 128, tagf(d0[2] + d1[2], par), tagf(d0[3] + d1[3], par));
      }
    }
    return;
  }

  const int h = cta >> 2, j = cta & 3, pr = cta >> 1, rk = cta & 1, bb = cta >> 5;

  if (tid < 288) sts128(sb + Y3_OFF + tid * 16, xx);
  bar_sync(1, 512);

  if (warp < 12) {
    if (cta < 108 && warp < 6) {
      const int col = (cta % 18) * 32 + lane;
      char* dst = G + (U_MOD1 + (col / 144) * 2 + (cta % 36) / 18) * 8192 + (warp & 1) * 4096 + (cta / 36) * 1152 + (col % 144) * 8;
      if (warp < 2) stg_rlx64(dst, par ^ 1u, 0);
      float d[4] = {0, 0, 0, 0}, e[4] = {0, 0, 0, 0};
      const uint32_t aoff = sb + M1_OFF + (warp * 32 + (lane >> 4) * 8 + (lane & 7)) * 64 + ((((lane >> 3) & 1) ^ ((lane >> 1) & 3)) << 4);
      uint32_t a[4][4], b[4];
      ldsm4(b, sb + ACT_OFF + (lane & 3) * ACT_P + (lane >> 3) * 16 + ((cta / 36) * 192 + warp * 32) * 2);
      mbar_wait(bars + 8 * B_M1, 0);
#pragma unroll
      for (int q = 0; q < 4; q++) ldsm4t(a[q], (aoff ^ ((q >> 1) * 32)) + (q & 1) * 1024);
      mma16(d, a[0], b[0], b[1]); mma16(e, a[2], b[0], b[1]); mma16(d, a[1], b[2], b[3]); mma16(e, a[3], b[2], b[3]);
      const uint32_t ra = sb + RED_OFF + (warp * 128 + (t >> 1) * 32 + g * 4 + (t & 1) * 2) * 4;
      sts64f(ra, t < 2 ? d[0] : d[2], t < 2 ? d[1] : d[3]);
      sts64f(ra + 256, t < 2 ? e[0] : e[2], t < 2 ? e[1] : e[3]);
      bar_sync(2, 192);
      if (warp < 2) {
        uint4 v[6];
#pragma unroll
        for (int w = 0; w < 6; w++) v[w] = lds128(sb + RED_OFF + w * 512 + lane * 16);
        const float s0 = ((UF(v[0].x) + UF(v[1].x)) + (UF(v[2].x) + UF(v[3].x))) + (UF(v[4].x) + UF(v[5].x));
        const float s1 = ((UF(v[0].y) + UF(v[1].y)) + (UF(v[2].y) + UF(v[3].y))) + (UF(v[4].y) + UF(v[5].y));
        const float s2 = ((UF(v[0].z) + UF(v[1].z)) + (UF(v[2].z) + UF(v[3].z))) + (UF(v[4].z) + UF(v[5].z));
        const float s3 = ((UF(v[0].w) + UF(v[1].w)) + (UF(v[2].w) + UF(v[3].w))) + (UF(v[4].w) + UF(v[5].w));
        stg_rlx64(dst, tagb(pack_bf16(s0, s1), par), pack_bf16(s2, s3));
      }
    }
  } else {
    const int b = warp - 12;
    float v[18], s = 0.f;
#pragma unroll
    for (int i = 0; i < 9; i++) {
      uint32_t w = lds32(sb + Y3_OFF + b * 1152 + (i * 32 + lane) * 4);
      v[2 * i] = bf_lo(w); v[2 * i + 1] = bf_hi(w); s += v[2 * i] + v[2 * i + 1];
    }
#pragma unroll
    for (int o = 16; o; o >>= 1) s += __shfl_xor_sync(0xffffffffu, s, o);
    const float mean = s * (1.f / 576.f);
    float q = 0.f;
#pragma unroll
    for (int i = 0; i < 18; i++) { float dd = v[i] - mean; q += dd * dd; }
#pragma unroll
    for (int o = 16; o; o >>= 1) q += __shfl_xor_sync(0xffffffffu, q, o);
    if (lane == 0) sts64f(sb + ST_OFF + b * 8, mean, rsqrtf(q * (1.f / 576.f) + 1e-5f));
  }
  if (warp == 0 && cta < 72) {
    uint32_t w = lds32(sb + Y3_OFF + t * 1152 + ((cta * 8 + g) >> 1) * 4);
    sts32f(sb + ST_OFF + 768 + lane * 4, (g & 1) ? bf_hi(w) : bf_lo(w));
  }
  bar_sync(1, 512);

  {
    const uint4 z = make_uint4(par ^ 1u, 0, par ^ 1u, 0);
    if (warp < 8) stg_rlx(G + (U_Q + h * 2 + (tid >> 7)) * 8192 + ((tid >> 6) & 1) * 4096 + j * 1024 + (tid & 63) * 16, z);
    else if (warp >= 13) {
      if (warp < 15) {
        const int u = tid - 416;
        char* d = G + (U_QA + ((u >> 4) * 2 + (j >> 1)) * 4 + (h >> 3)) * 8192 + (h & 7) * 512 + (j & 1) * 256 + (u & 15) * 16;
        stg_rlx(d, z); stg_rlx(d + 4096, z);
      } else if (cta < 72 && lane < 16) stg_rlx(G + (U_X2 + cta / 24) * 8192 + (lane >> 3) * 4096 + (cta % 24) * 128 + (lane & 7) * 16, z);
      __syncwarp();
    }
  }
  int p0 = (int)lds32v(sb + ST_OFF + 64) & 1;

  uint32_t afr[9][4];
  if (warp < 8) {
    mbar_wait4(bars + 8 * B_WQ, bars + 8 * B_WQ + 8, bars + 8 * B_WQ + 16, bars + 8 * B_WQ + 24);
    const int ch = (warp & 3) * 2 + ((lane >> 3) & 1), row = (lane >> 4) * 8 + (lane & 7);
    const uint32_t a = sb + Y1_OFF + (warp >> 2) * 18432 + row * 128 + ((ch ^ (lane & 7)) << 4);
#pragma unroll
    for (int ks = 0; ks < 9; ks++) ldsm4t(afr[ks], a + ks * 2048);
  } else if (warp < 13) {
    const int k = min(tid - 256, 142 + (tid & 1)), col = j * 144 + k;
    float nx[4];
#pragma unroll
    for (int b = 0; b < 4; b++) {
      uint32_t w = lds32(sb + Y3_OFF + b * 1152 + (col >> 1) * 4);
      uint2 st = lds64(sb + ST_OFF + b * 8);
      nx[b] = (((col & 1) ? bf_hi(w) : bf_lo(w)) - UF(st.x)) * UF(st.y);
    }
    uint32_t sa_ = sb + AC2_OFF + k * 2;
    KEEP(sa_);
    WAIT_UNTIL(T_E1);
    while (!lds32v(sb + ST_OFF + 64) && (int)(gtime32() - t0) < T_E1B) ;
    p0 = (int)lds32v(sb + ST_OFF + 64) & 1;
    const char* src = NEAR(U_MOD1 + j * 2 + (k & 1)) + (k >> 1) * 16;
    uint4 v[3];
#pragma unroll
    for (int q = 0; q < 3; q++) v[q] = make_uint4(par ^ 1u, 0, 0, 0);
#pragma unroll 1
    for (int it = 0; it < SPIN_LIMIT; it++) {
      const bool b0 = !ok2(v[0], par), b1 = !ok2(v[1], par), b2 = !ok2(v[2], par);
      if (!__any_sync(0xffffffffu, b0 || b1 || b2)) break;
      ldg_rlx_if(b0, src, v[0]); ldg_rlx_if(b1, src + 1152, v[1]); ldg_rlx_if(b2, src + 2304, v[2]);
    }
    float c0[4], c1[4];
    c0[0] = bf_lo(v[0].x & ~1u) + bf_lo(v[1].x & ~1u) + bf_lo(v[2].x & ~1u); c0[1] = bf_hi(v[0].x) + bf_hi(v[1].x) + bf_hi(v[2].x);
    c0[2] = bf_lo(v[0].y) + bf_lo(v[1].y) + bf_lo(v[2].y); c0[3] = bf_hi(v[0].y) + bf_hi(v[1].y) + bf_hi(v[2].y);
    c1[0] = bf_lo(v[0].z & ~1u) + bf_lo(v[1].z & ~1u) + bf_lo(v[2].z & ~1u); c1[1] = bf_hi(v[0].z) + bf_hi(v[1].z) + bf_hi(v[2].z);
    c1[2] = bf_lo(v[0].w) + bf_lo(v[1].w) + bf_lo(v[2].w); c1[3] = bf_hi(v[0].w) + bf_hi(v[1].w) + bf_hi(v[2].w);
    const bool odd = k & 1;
#pragma unroll
    for (int b = 0; b < 4; b++) {
      const float o = __shfl_xor_sync(0xffffffffu, odd ? c0[b] : c1[b], 1);
      const float sa = odd ? o : c0[b], ca = odd ? c1[b] : o;
      sts16(sa_ + b * AC2_P, to_bf16(nx[b] * (1.f + ca) + sa));
    }
  }
  uint32_t bo0 = sb + AC2_OFF + (lane & 3) * AC2_P + (lane >> 3) * 16;
  {
    char* dst = G + (U_Q + h * 2 + ((warp >> 2) & 1)) * 8192 + (t >> 1) * 4096 + j * 1024 + ((warp & 3) * 16 + g) * 16 + (t & 1) * 8;
    PIN(bo0); KEEPL(dst);
    bar_sync(1, 512);

    if (warp < 8) {
      float d0[4] = {0, 0, 0, 0}, d1[4] = {0, 0, 0, 0}, d2[4] = {0, 0, 0, 0};
      uint32_t b[5][4];
#pragma unroll
      for (int q = 0; q < 4; q++) ldsm4(b[q], bo0 + q * 64);
      ldsm4(b[4], bo0 + 256 - (lane >> 4) * 32);
#pragma unroll
      for (int ks = 0; ks < 9; ks += 3) {
        mma16(d0, afr[ks], b[ks >> 1][(ks & 1) * 2], b[ks >> 1][(ks & 1) * 2 + 1]);
        mma16(d1, afr[ks + 1], b[(ks + 1) >> 1][((ks + 1) & 1) * 2], b[(ks + 1) >> 1][((ks + 1) & 1) * 2 + 1]);
        mma16(d2, afr[ks + 2], b[(ks + 2) >> 1][((ks + 2) & 1) * 2], b[(ks + 2) >> 1][((ks + 2) & 1) * 2 + 1]);
      }
      stg_rlx64(dst, tagf(d0[0] + d1[0] + d2[0], par), __float_as_uint(d0[1] + d1[1] + d2[1]));
      stg_rlx64(dst + 128, tagf(d0[2] + d1[2] + d2[2], par), __float_as_uint(d0[3] + d1[3] + d2[3]));
    } else {
      mbar_wait4(bars + 8 * B_WUK, bars + 8 * B_WUK + 8, bars + 8 * B_WUK + 16, bars + 8 * B_WUK + 24);
      const int rho = lane & 7;
      const int row = (warp - 8) * 16 + 4 * (rho >> 1) + 2 * ((lane >> 3) & 1) + (rho & 1);
      const uint32_t a = sb + Y2_OFF + row * 128;
#pragma unroll
      for (int ks = 0; ks < 8; ks++) ldsm4(afr[ks], a + (ks >> 2) * 16384 + ((((ks & 3) * 2 + (lane >> 4)) ^ (row & 7)) << 4));
    }
  }
  if (lane == 0) mbar_arrive(bars + 8 * B_QDONE);
  __syncwarp();

  p0 = (int)lds32v(sb + ST_OFF + 64) & 1;
  {
    char* dst = G + (U_QA + ((g & 3) * 2 + (j >> 1)) * 4 + (h >> 3)) * 8192 + (g >> 2) * 4096 + (h & 7) * 512 + (j & 1) * 256 + (warp & 7) * 32 + t * 8;
    KEEPL(dst);
    if (warp < 8) {
      const int d = warp * 8 + g;
      const char* src0 = NEAR(U_Q + h * 2) + t * 1024 + d * 16;
      const char* src1 = NEAR(U_Q + h * 2 + 1) + t * 1024 + d * 16;
      uint32_t sa_ = sb + AC2_OFF + (4 + t) * AC2_P + d * 2;
      KEEP(sa_);
      uint4 v0, v1;
      poll16x2(src0, src1, par, v0, v1);
      const float s0 = xreduce4<2, 1>(UF(v0.x), UF(v0.y), UF(v0.z), UF(v0.w), lane);
      const float s1 = xreduce4<2, 1>(UF(v1.x), UF(v1.y), UF(v1.z), UF(v1.w), lane);
      sts16(sa_, to_bf16(s0));
      sts16(sa_ + 128, to_bf16(s1));
    }
    bar_sync(1, 512);

    if (warp >= 8) {
      float d0[4] = {0, 0, 0, 0}, d1[4] = {0, 0, 0, 0}, d2[4] = {0, 0, 0, 0}, d3[4] = {0, 0, 0, 0};
      uint32_t b[4][4];
#pragma unroll
      for (int q = 0; q < 4; q++) ldsm4(b[q], bo0 + 4 * AC2_P + q * 64);
#pragma unroll
      for (int q = 0; q < 4; q += 2) {
        mma16(d0, afr[2 * q], b[q][0], b[q][1]);
        mma16(d1, afr[2 * q + 1], b[q][2], b[q][3]);
        mma16(d2, afr[2 * q + 2], b[q + 1][0], b[q + 1][1]);
        mma16(d3, afr[2 * q + 3], b[q + 1][2], b[q + 1][3]);
      }
      const float sc = 0.08838834764831845f * 1.4426950408889634f;
      uint32_t p0 = pack_bf16(((d0[0] + d1[0]) + (d2[0] + d3[0])) * sc, ((d0[1] + d1[1]) + (d2[1] + d3[1])) * sc);
      uint32_t p1 = pack_bf16(((d0[2] + d1[2]) + (d2[2] + d3[2])) * sc, ((d0[3] + d1[3]) + (d2[3] + d3[3])) * sc);
      uint32_t q0, q1;
      asm volatile("movmatrix.sync.aligned.m8n8.trans.b16 %0, %1;" : "=r"(q0) : "r"(p0));
      asm volatile("movmatrix.sync.aligned.m8n8.trans.b16 %0, %1;" : "=r"(q1) : "r"(p1));
      stg_rlx64(dst, tagb(q0, par), q1);
    }
  }
  asm volatile("barrier.cluster.arrive.relaxed.aligned;" ::: "memory");

  {
    const int hd = tid >> 4, u = tid & 15;
    const char* src = NEAR(U_QA + (bb * 2 + rk) * 4 + (hd >> 3)) + (hd & 7) * 512 + u * 16;
    uint32_t a = sb + Y3_OFF + (u >> 3) * 4096 + hd * 128 + (((u & 7) ^ (hd & 7)) << 4);
    KEEP(a);
    uint4 v0, v1;
    poll16x2(src, src + 256, par, v0, v1);
    v0.x &= ~1u; v0.z &= ~1u; v1.x &= ~1u; v1.z &= ~1u;
    sts128(a, v0);
    sts128(a + 8192, v1);
    fence_async();
    __syncwarp();
  }
  asm volatile("barrier.cluster.wait.aligned;" ::: "memory");
  bar_sync(1, 512);

  {
    const int wg = warp >> 2, wq = warp & 3, tl = tid & 127;
    float acc[16];
#pragma unroll
    for (int e = 0; e < 16; e++) acc[e] = 0.f;
    const uint32_t rbuf = sb + Y2_OFF + wg * 8192;
    float s[16];
    const uint32_t fa = sb + SMX_OFF + 512 + 2 * t * 4;
    const uint64_t dpa = mkdesc(sb + X_OFF + wg * 8192, 1024, 1), dpb = mkdesc(sb + Y2_OFF, 512, 2);
    auto pv_issue = [&](int i, bool real = true) {
      const uint64_t da = dpa + i * 2048, db = dpb + i * 512;
      mbar_wait2(bars + 8 * (real ? B_PRDY + i : B_DONE), bars + 8 * (B_CKV + i * 4 + wg));
      uint2 f[4];
#pragma unroll
      for (int q = 0; q < 4; q++) f[q] = lds64(fa + i * 128 + q * 32);
#pragma unroll
      for (int q = 0; q < 4; q++) { acc[4 * q] *= UF(f[q].x); acc[4 * q + 1] *= UF(f[q].y); acc[4 * q + 2] *= UF(f[q].x); acc[4 * q + 3] *= UF(f[q].y); }
      wg_fence();
#pragma unroll
      for (int ks = 0; ks < 4; ks++) wgmma_n32<1, 1>(acc, da + ks * 128, db + ks * 64, ks | i);
      wg_commit();
    };
    auto pv_done = [&](int i) { wg_wait0(); if (lane == 0) mbar_arrive(bars + 8 * (B_TFREE + i)); };
    int ip = 0;
#pragma unroll 1
    for (int it = 0; ip < wg - 1 && it < SPIN_LIMIT; it++) {
      uint32_t st;
      asm volatile("{\n.reg .pred p, q, r, u;\n"
                   "mbarrier.test_wait.parity.shared::cta.b64 p, [%1], 0;\n"
                   "mbarrier.test_wait.parity.shared::cta.b64 r, [%2], 0;\n"
                   "bar.red.and.pred q, %3, 128, p;\n"
                   "bar.red.and.pred u, %3, 128, r;\n"
                   "selp.u32 %0, 2, 0, u;\n@q mov.u32 %0, 1;\n}"
                   : "=r"(st) : "r"(bars + 8 * (B_CKV + wg * 4 + 2)), "r"(bars + 8 * (B_PRDY + ip)), "r"(4 + wg) : "memory");
      st = __shfl_sync(0xffffffffu, st, 0);
      if (st == 1) break;
      if (st == 2) { pv_issue(ip); pv_done(ip); ip++; }
    }
    {
      uint32_t rem, rbar;
      asm volatile("mapa.shared::cluster.u32 %0, %1, %2;" : "=r"(rem) : "r"(rbuf + tl * 16), "r"(rk ^ 1));
      asm volatile("mapa.shared::cluster.u32 %0, %1, %2;" : "=r"(rbar) : "r"(bars + 8 * (B_SRECV + wg)), "r"(rk ^ 1));
      float qs[16];
#pragma unroll
      for (int e = 0; e < 16; e++) qs[e] = 0.f;
#pragma unroll
      for (int sl = 0; sl < 4; sl++) {
        const uint64_t da = mkdesc(sb + X_OFF + (wg * 4 + sl) * 8192, 1024, 1);
        const uint64_t db = mkdesc(sb + Y3_OFF + sl * 4096, 1024, 1);
        mbar_wait(bars + 8 * (B_CKV + wg * 4 + sl), 0);
        wg_fence();
#pragma unroll
        for (int kk = 0; kk < 4; kk++) wgmma_n32<0, 0>(qs, da + kk * 2, db + kk * 2, 1);
        wg_commit();
      }
      wg_wait0();
#pragma unroll
      for (int q = 0; q < 4; q++)
        asm volatile("st.async.shared::cluster.mbarrier::complete_tx::bytes.v4.f32 [%0], {%1,%2,%3,%4}, [%5];"
                     :: "r"(rem + q * 2048), "f"(qs[4 * q]), "f"(qs[4 * q + 1]), "f"(qs[4 * q + 2]), "f"(qs[4 * q + 3]), "r"(rbar) : "memory");
#pragma unroll
      for (int e = 0; e < 16; e++) asm volatile("mov.b32 %0, %1;" : "=f"(s[e]) : "f"(qs[e]));
    }
#pragma unroll 1
    for (; ip < wg - 1; ip++) { pv_issue(ip); pv_done(ip); }
    pv_issue(max(wg - 1, 0), wg > 0);
    const int myhead = (lane & 24) + 2 * t + (g & 1);
    uint32_t oa0 = 0, oa1 = 0;
    auto dests = [&]() {
      mbar_wait(bars + 8 * B_MASK, 0);
      const int c0 = (tl >> 3) * 4 + rk * 2 + (wg >> 1);
      oa0 = BLK_G + c0 * 65536 + bb * 16384 + (hsel(sb, c0) << 12) + (pr & 15) * 256 + (wg & 1) * 128 + (tl & 7) * 16;
      oa1 = BLK_G + (c0 + 64) * 65536 + bb * 16384 + (hsel(sb, c0 + 64) << 12) + (pr & 15) * 256 + (wg & 1) * 128 + (tl & 7) * 16;
    };
    if (wg == 3) dests();
    {
      const uint32_t amax = sb + SMX_OFF + (wg * 32 + myhead) * 4, amx2 = sb + SMX_OFF + (wg * 32 + 2 * t) * 4;
      const uint32_t pb = rbuf + (wq * 16 + g) * 64 + t * 4 + ((g >> 1) << 4), rb = rbuf + tl * 16;
      const int kprev = wg > 0 ? (int)lds32(amax - 128) : (int)0x80000000;
      mbar_wait(bars + 8 * (B_SRECV + wg), 0);
      float mx[8];
      {
        uint4 v[4];
#pragma unroll
        for (int q = 0; q < 4; q++) v[q] = lds128(rb + q * 2048);
#pragma unroll
        for (int q = 0; q < 4; q++) {
          s[4 * q] += UF(v[q].x); s[4 * q + 1] += UF(v[q].y); s[4 * q + 2] += UF(v[q].z); s[4 * q + 3] += UF(v[q].w);
          mx[2 * q] = fmaxf(s[4 * q], s[4 * q + 2]); mx[2 * q + 1] = fmaxf(s[4 * q + 1], s[4 * q + 3]);
        }
      }
      const int key = max(fkey(xreduce8<true>(mx, lane)), kprev);
      asm volatile("red.shared.max.s32 [%0], %1;" :: "r"(amax), "r"(key) : "memory");
      bar_sync(4 + wg, 128);
      uint2 mk[4];
#pragma unroll
      for (int q = 0; q < 4; q++) mk[q] = lds64(amx2 + q * 32);
      const int kcur = (int)lds32(amax);
      const float fac = wg > 0 ? ex2(funkey(kprev) - funkey(kcur)) : 0.f;
      uint32_t pk[8];
#pragma unroll
      for (int q = 0; q < 4; q++) {
        const float m0 = funkey((int)mk[q].x), m1 = funkey((int)mk[q].y);
        const float p0 = ex2(s[4 * q] - m0), p1 = ex2(s[4 * q + 1] - m1), p2 = ex2(s[4 * q + 2] - m0), p3 = ex2(s[4 * q + 3] - m1);
        pk[2 * q] = pack_bf16(p0, p1); pk[2 * q + 1] = pack_bf16(p2, p3);
      }
      sts32f(amax + 512, fac);
#pragma unroll
      for (int q = 0; q < 4; q++) { sts32(pb ^ (q << 4), pk[2 * q]); sts32((pb ^ (q << 4)) + 512, pk[2 * q + 1]); }
      fence_async();
      __syncwarp();
      if (lane == 0) mbar_arrive(bars + 8 * (B_PRDY + wg));
    }
    wg_wait0();
    if (wg > 0 && lane == 0) mbar_arrive(bars + 8 * (B_TFREE + wg - 1));
    pv_issue(wg);
    if (wg < 3) {
      pv_done(wg);
#pragma unroll 1
      for (int i = wg + 1; i < 3; i++) { pv_issue(i); pv_done(i); }
      dests();
      pv_issue(3);
    }
    pv_done(3);
    const uint32_t stg = sb + Y3_OFF + wg * 4096;
#pragma unroll
    for (int hf = 0; hf < 2; hf++) {
      uint32_t r0 = pack_bf16(acc[2 * hf], acc[2 * hf + 1]), r1 = pack_bf16(acc[4 + 2 * hf], acc[5 + 2 * hf]);
      uint32_t r2 = pack_bf16(acc[8 + 2 * hf], acc[9 + 2 * hf]), r3 = pack_bf16(acc[12 + 2 * hf], acc[13 + 2 * hf]);
      const uint32_t a = stg + lane * 128 + (((wq * 2 + hf) ^ (lane & 7)) << 4);
      asm volatile("stmatrix.sync.aligned.m8n8.x4.trans.shared.b16 [%0], {%1,%2,%3,%4};" :: "r"(a), "r"(r0), "r"(r1), "r"(r2), "r"(r3) : "memory");
    }
    bar_sync(4 + wg, 128);
    {
      const int hd = tl >> 3, ch = tl & 7;
      uint4 v0 = lds128(stg + hd * 128 + ((ch ^ (hd & 7)) << 4)), v1 = lds128(stg + 2048 + hd * 128 + ((ch ^ (hd & 7)) << 4));
      v0.x = tagb(v0.x, 1u); v0.z = tagb(v0.z, 1u); v1.x = tagb(v1.x, 1u); v1.z = tagb(v1.z, 1u);
      stg_rlx(G + oa0, v0);
      stg_rlx(G + oa1, v1);
    }
  }

  uint32_t auv[8][4];
  if (warp < 8) {
    mbar_wait4(bars + 8 * B_WUV, bars + 8 * B_WUV + 8, bars + 8 * B_WUV + 16, bars + 8 * B_WUV + 24);
    const int ch = (warp & 3) * 2 + ((lane >> 3) & 1), row = (lane >> 4) * 8 + (lane & 7);
    const uint32_t a = sb + Y1_OFF + (warp >> 2) * 16384 + row * 128 + ((ch ^ (lane & 7)) << 4);
#pragma unroll
    for (int ks = 0; ks < 8; ks++) ldsm4t(auv[ks], a + ks * 2048);
  }
  const uint32_t myh = hsel(sb, cta);
  char* const blk = G + BLK_G + cta * 65536;
  {
    const int b = warp >> 2, cq = warp & 3;
    const char* mlp = blk + 5 * 8192 + ((myh ^ 1u) << 12) + 2048 + (b * 16 + g) * 32;
    const char* src = blk + b * 16384 + (myh << 12) + g * 256 + cq * 64 + t * 16;
    uint32_t sa_ = sb + AC2_OFF + b * AC2_P + (cq * 32 + t * 8 + g) * 2;
    const int cc = h * 4 + ((warp >> 1) & 3);
    char* dst = G + BLK_G + cc * 65536 + 5 * 8192 + ((hsel(sb, cc) ^ 1u) << 12) + j * 512 + ((warp & 1) * 16 + (t >> 1) * 8 + g) * 16 + (t & 1) * 8;
    KEEP(sa_); KEEPL(src); KEEPL(dst);
    uint2 ml0 = make_uint2(0, 0), ml1 = ml0;
    uint4 v0 = make_uint4(0, 0, 0, 0), v1 = v0;
#pragma unroll 1
    for (int it = 0; it < SPIN_LIMIT; it++) {
      const bool b0 = !(v0.x & v0.z & 1u), b1 = !(v1.x & v1.z & 1u), c0 = !(ml0.x & 1u), c1 = !(ml1.x & 1u);
      const unsigned m0 = __ballot_sync(0xffffffffu, b0), m1 = __ballot_sync(0xffffffffu, b1);
      if (!(m0 | m1) && !__any_sync(0xffffffffu, c0 || c1)) break;
      if (__popc(m0) + __popc(m1) > TH4) {
        const char* lp = (const char*)__shfl_sync(0xffffffffu, (unsigned long long)(m0 ? src : src + 2048), __ffs(m0 ? m0 : m1) - 1);
#pragma unroll 1
        for (; it < SPIN_LIMIT; it++) if (ldg_rlx32(lp) & 1u) break;
      }
      if (c0) ml0 = ldg_rlx64(mlp);
      if (c1) ml1 = ldg_rlx64(mlp + 256);
      ldg_rlx_if(b0, src, v0);
      ldg_rlx_if(b1, src + 2048, v1);
    }
    float mm = fmaxf(UF(ml0.y), UF(ml1.y));
#pragma unroll
    for (int o = 16; o >= 4; o >>= 1) mm = fmaxf(mm, __shfl_xor_sync(0xffffffffu, mm, o));
    const float w0 = ex2(UF(ml0.y) - mm), w1 = ex2(UF(ml1.y) - mm);
    float l = w0 * UF(ml0.x) + w1 * UF(ml1.x);
#pragma unroll
    for (int o = 16; o >= 4; o >>= 1) l += __shfl_xor_sync(0xffffffffu, l, o);
    v0.x &= ~1u; v0.z &= ~1u; v1.x &= ~1u; v1.z &= ~1u;
    float a[8];
    a[0] = w0 * bf_lo(v0.x) + w1 * bf_lo(v1.x); a[1] = w0 * bf_hi(v0.x) + w1 * bf_hi(v1.x);
    a[2] = w0 * bf_lo(v0.y) + w1 * bf_lo(v1.y); a[3] = w0 * bf_hi(v0.y) + w1 * bf_hi(v1.y);
    a[4] = w0 * bf_lo(v0.z) + w1 * bf_lo(v1.z); a[5] = w0 * bf_hi(v0.z) + w1 * bf_hi(v1.z);
    a[6] = w0 * bf_lo(v0.w) + w1 * bf_lo(v1.w); a[7] = w0 * bf_hi(v0.w) + w1 * bf_hi(v1.w);
    sts16(sa_, to_bf16(__fdividef(xreduce8<false>(a, lane), l)));
    bar_sync(1, 512);

    if (warp < 8) {
      float d0[4] = {0, 0, 0, 0}, d1[4] = {0, 0, 0, 0}, d2[4] = {0, 0, 0, 0}, d3[4] = {0, 0, 0, 0};
      uint32_t bf[4][4];
#pragma unroll
      for (int q = 0; q < 4; q++) ldsm4(bf[q], bo0 + q * 64);
#pragma unroll
      for (int q = 0; q < 4; q += 2) {
        mma16(d0, auv[2 * q], bf[q][0], bf[q][1]);
        mma16(d1, auv[2 * q + 1], bf[q][2], bf[q][3]);
        mma16(d2, auv[2 * q + 2], bf[q + 1][0], bf[q + 1][1]);
        mma16(d3, auv[2 * q + 3], bf[q + 1][2], bf[q + 1][3]);
      }
      stg_rlx64(dst, tagf(t < 2 ? (d0[0] + d1[0]) + (d2[0] + d3[0]) : (d0[2] + d1[2]) + (d2[2] + d3[2]), 1u),
                __float_as_uint(t < 2 ? (d0[1] + d1[1]) + (d2[1] + d3[1]) : (d0[3] + d1[3]) + (d2[3] + d3[3])));
      if (lane == 0) mbar_arrive(bars + 8 * B_UVF);
    }
  }
  uint32_t roff[3];
  const char* rsrc;
  auto slots = [&]() {
#pragma unroll
    for (int m = 0; m < 3; m++) {
      const int u = min((warp * 3 + m) * 2 + (t & 1), 71);
      roff[m] = BLK_G + u * 65536 + (1 + (cta >> 6) * 2) * 8192 + ((hsel(sb, u) ^ 1u) << 12) + (cta & 63) * 64 + g * 8;
    }
    rsrc = blk + (1 + (warp >> 3) * 2) * 8192 + ((hsel(sb, cta) ^ 1u) << 12) + (tid & 255) * 16;
  };
  slots();
  {
    uint32_t awo[6][4];
    if (warp < 12) {
      mbar_wait(bars + 8 * (B_WO + (warp >> 2)), 0);
      const int row = (lane >> 4) * 8 + (lane & 7);
#pragma unroll
      for (int m = 0; m < 3; m++) {
        const int mt = warp * 3 + m, ch = (mt & 3) * 2 + ((lane >> 3) & 1);
        const uint32_t a = sb + WO_OFF + (mt >> 2) * 4096 + row * 128 + ((ch ^ (lane & 7)) << 4);
        ldsm4t(awo[2 * m], a);
        ldsm4t(awo[2 * m + 1], a + 2048);
      }
    } else {
      const int dl = (warp - 12) * 8 + g;
      uint32_t sa_ = sb + AC2_OFF + (4 + t) * AC2_P + dl * 2;
      KEEP(sa_);
      const uint4 v = poll16(blk + 5 * 8192 + ((myh ^ 1u) << 12) + t * 512 + dl * 16, 1u);
      sts16(sa_, to_bf16(xreduce4<2, 1>(UF(v.x), UF(v.y), UF(v.z), UF(v.w), lane)));
    }
    bar_sync(1, 512);

    if (warp < 12) {
      uint32_t bq[4];
      ldsm4(bq, bo0 + 4 * AC2_P);
      const uint32_t b0 = bq[0], b1 = bq[1], b2 = bq[2], b3 = bq[3];
      float d[3][4] = {{0, 0, 0, 0}, {0, 0, 0, 0}, {0, 0, 0, 0}};
#pragma unroll
      for (int m = 0; m < 3; m++) mma16(d[m], awo[2 * m], b0, b1);
#pragma unroll
      for (int m = 0; m < 3; m++) mma16(d[m], awo[2 * m + 1], b2, b3);
      send_pieces(G, roff, d, t, 1u);
    }
  }

  if (cta < 72) {
    char* dst = G + (U_X2 + cta / 24) * 8192 + (lane & 1) * 4096 + (cta % 24) * 128 + (lane >> 1) * 8;
    KEEPL(dst);
    DELAY(D_E6);
    reduce_pieces(rsrc, 1u, sb, warp, lane, bars + 8 * B_GA, sb + ST_OFF + 768, sb + ST_OFF + 512, [&](float x2) {
      const float nb = __shfl_xor_sync(0xffffffffu, x2, 1);
      stg_rlx64(dst, tagf((lane & 1) ? nb : x2, par), __float_as_uint((lane & 1) ? x2 : nb));
      sts32f(sb + ST_OFF + 768 + lane * 4, x2);
    });
  }

  const bool wide = cta & 8;
  {
    const int gu_u = warp % 5, gu_t = warp / 5;
    uint32_t agu[12][4];
    uint32_t bo = sb + ACT_OFF + (lane & 3) * ACT_P + (lane >> 3) * 16 + gu_t * 384 + ((lane >> 2) & 1) * 192;
    PIN(bo);
    const int nown = wide ? 5 : 4, unit = gu_u * 2 + (t >> 1), own = unit >= nown;
    uint32_t ra, rbar;
    asm volatile("mapa.shared::cluster.u32 %0, %1, %2;" : "=r"(ra) : "r"(sb + SC_OFF + 9216 + (((unit - own * nown) * 2 + rk) * 3 + gu_t) * 128 + g * 16 + (t & 1) * 8), "r"(own));
    asm volatile("mapa.shared::cluster.u32 %0, %1, %2;" : "=r"(rbar) : "r"(bars + 8 * B_ACT), "r"(own));
    const uint32_t gp = wide ? 160 : 128;
    const uint32_t ga = sb + GA_OFF + (gu_t * 192 + (lane >> 4) * 8 + (lane & 7)) * gp +
                        (wide ? gu_u * 2 + ((lane >> 3) & 1) : ((gu_u * 2 + ((lane >> 3) & 1)) ^ lane) & 7) * 16;
    const uint32_t gb = bars + 8 * (B_GU + gu_t * 4);
    p0 = (int)lds32v(sb + ST_OFF + 64) & 1;
    bool have_w = false;
    if (warp >= 9) {
      if (warp < 15) {
        mbar_wait4(gb, gb + 8, gb + 16, gb + 24);
#pragma unroll
        for (int ks = 0; ks < 12; ks++) ldsm4t(agu[ks], ga + ks * 16 * gp);
      }
    } else {
      const char* x0 = NEAR(U_X2 + tid / 192) + (tid % 192) * 16;
      const char* x1 = NEAR(U_X2 + (tid + 288) / 192) + ((tid + 288) % 192) * 16;
      const char* xk = NEAR(U_X2) + (cta % 24) * 128;
      uint32_t sa_ = sb + ACT_OFF + tid * 2, sp = sb + ST_OFF + 128 + (warp * 8 + g) * 4, sr = sb + ST_OFF + 128 + (lane & 7) * 4;
      uint4 v0, v1, vk;
#pragma unroll 1
      for (int it = 0; it < SPIN_LIMIT; it++) {
        vk = ldg_rlx(xk);
        if (!have_w && __all_sync(0xffffffffu, mbar_test4(gb, gb + 8, gb + 16, gb + 24))) {
          have_w = true;
#pragma unroll
          for (int ks = 0; ks < 12; ks++) ldsm4t(agu[ks], ga + ks * 16 * gp);
        }
        if (__all_sync(0xffffffffu, ok2(vk, par))) break;
      }
      v0 = ldg_rlx(x0); v1 = ldg_rlx(x1);
      mbar_wait(bars + 8 * B_SC, 0);
      poll_fin2(x0, x1, par, v0, v1);
      const float xa[4] = {UF(v0.x) - UF(vk.x), UF(v0.y) - UF(vk.y), UF(v0.z) - UF(vk.z), UF(v0.w) - UF(vk.w)};
      const float xb[4] = {UF(v1.x) - UF(vk.x), UF(v1.y) - UF(vk.y), UF(v1.z) - UF(vk.z), UF(v1.w) - UF(vk.w)};
      float st[8];
#pragma unroll
      for (int b = 0; b < 4; b++) { st[2 * b] = xa[b] + xb[b]; st[2 * b + 1] = xa[b] * xa[b] + xb[b] * xb[b]; }
      float z = xreduce8<false>(st, lane);
      z += __shfl_xor_sync(0xffffffffu, z, 2);
      z += __shfl_xor_sync(0xffffffffu, z, 1);
      sts32f(sp, z);
      const uint4 sc0 = lds128(sb + SC_OFF + tid * 16), sc1 = lds128(sb + SC_OFF + (288 + tid) * 16);
      const float sh0[4] = {bf_lo(sc0.x), bf_hi(sc0.x), bf_lo(sc0.y), bf_hi(sc0.y)}, sh1[4] = {bf_lo(sc1.x), bf_hi(sc1.x), bf_lo(sc1.y), bf_hi(sc1.y)};
      const float cs0[4] = {1.f + bf_lo(sc0.z), 1.f + bf_hi(sc0.z), 1.f + bf_lo(sc0.w), 1.f + bf_hi(sc0.w)};
      const float cs1[4] = {1.f + bf_lo(sc1.z), 1.f + bf_hi(sc1.z), 1.f + bf_lo(sc1.w), 1.f + bf_hi(sc1.w)};
      bar_sync(2, 288);
      float pv[9];
#pragma unroll
      for (int w = 0; w < 9; w++) pv[w] = lds32f(sr + w * 32);
      float tot = (((pv[0] + pv[1]) + (pv[2] + pv[3])) + ((pv[4] + pv[5]) + (pv[6] + pv[7])) + pv[8]) * (1.f / 576.f);
      const float oth = __shfl_xor_sync(0xffffffffu, tot, 1);
      float rq;
      asm("rsqrt.approx.ftz.f32 %0, %1;" : "=f"(rq) : "f"(fmaxf(tot - oth * oth, 0.f) + 1e-5f));
      tot = (lane & 1) ? rq : tot;
      float mean[4], rs[4];
#pragma unroll
      for (int b = 0; b < 4; b++) { mean[b] = __shfl_sync(0xffffffffu, tot, 2 * b); rs[b] = __shfl_sync(0xffffffffu, tot, 2 * b + 1); }
#pragma unroll
      for (int b = 0; b < 4; b++) {
        sts16(sa_ + b * ACT_P, to_bf16((xa[b] - mean[b]) * rs[b] * cs0[b] + sh0[b]));
        sts16(sa_ + b * ACT_P + 576, to_bf16((xb[b] - mean[b]) * rs[b] * cs1[b] + sh1[b]));
      }
      if (!have_w) {
        mbar_wait4(gb, gb + 8, gb + 16, gb + 24);
#pragma unroll
        for (int ks = 0; ks < 12; ks++) ldsm4t(agu[ks], ga + ks * 16 * gp);
      }
    }
    bar_sync(1, 512);

    if (cta == 0 && tid == 480) asm volatile("red.relaxed.gpu.global.add.u32 [%0], 1;" :: "l"(G + EPOCH_G) : "memory");
    if (warp < 15) {
      float d0[4] = {0, 0, 0, 0}, d1[4] = {0, 0, 0, 0}, d2[4] = {0, 0, 0, 0}, d3[4] = {0, 0, 0, 0};
      uint32_t b[3][4];
#pragma unroll
      for (int q = 0; q < 3; q++) ldsm4(b[q], bo + q * 64);
#pragma unroll
      for (int q = 0; q < 3; q++) {
        mma16(d0, agu[2 * q], b[q][0], b[q][1]);
        mma16(d1, agu[2 * q + 1], b[q][2], b[q][3]);
        mma16(d2, agu[6 + 2 * q], b[q][0], b[q][1]);
        mma16(d3, agu[7 + 2 * q], b[q][2], b[q][3]);
      }
      const bool lo_ = t < 2;
      const float x0_ = __shfl_xor_sync(0xffffffffu, lo_ ? d0[2] + d1[2] : d2[0] + d3[0], 2);
      const float x1_ = __shfl_xor_sync(0xffffffffu, lo_ ? d0[3] + d1[3] : d2[1] + d3[1], 2);
      asm volatile("{\n.reg .pred p;\nsetp.lt.s32 p, %4, 0;\n@p st.async.shared::cluster.mbarrier::complete_tx::bytes.v2.f32 [%0], {%1,%2}, [%3];\n}"
                   :: "r"(ra), "f"(x0_ + (lo_ ? d0[0] + d1[0] : d2[2] + d3[2])), "f"(x1_ + (lo_ ? d0[1] + d1[1] : d2[3] + d3[3])), "r"(rbar), "r"(unit - 2 * nown) : "memory");
    }
  }
  {
    uint32_t a8[3][2], adn[6][4];
    slots();
    uint32_t bo1 = sb + AC2_OFF + (lane & 3) * AC2_P + (lane >> 3) * 16;
    PIN(bo1);
    uint32_t da[3];
#pragma unroll
    for (int m = 0; m < 3; m++) {
      const int mt = warp * 3 + m, ch = (mt & 3) * 2 + ((lane >> 3) & 1);
      da[m] = sb + DN_OFF + (mt >> 2) * (wide ? 5120 : 4096) + ((ch ^ (lane & 7)) << 4) + ((lane >> 4) * 8 + (lane & 7)) * 128;
      PIN(da[m]);
    }
    bool have_d = true;
    auto load_d = [&]() {
#pragma unroll
      for (int m = 0; m < 3; m++) {
        ldsm4t(adn[2 * m], da[m]);
        ldsm4t(adn[2 * m + 1], da[m] + 2048);
        ldsm2t(a8[m], da[m] + 4096);
      }
    };
    if (warp < 12) {
      have_d = __all_sync(0xffffffffu, mbar_test(bars + 8 * (B_DN + (warp >> 2)), 0));
      if (have_d) load_d();
    }
    if (warp >= 12 || (warp == 11 && wide)) {
      const uint32_t ra = sb + SC_OFF + 9216 + (15 - warp) * 768 + lane * 4, wa = sb + AC2_OFF + t * AC2_P + ((15 - warp) * 8 + g) * 2;
      mbar_wait(bars + 8 * B_ACT, 0);
      float v[6];
#pragma unroll
      for (int q = 0; q < 6; q++) v[q] = lds32f(ra + q * 128);
      sts16(wa, to_bf16(silu(v[0] + v[1] + v[2]) * (v[3] + v[4] + v[5])));
    }
    bar_sync(1, 512);

    if (warp < 12) {
      uint32_t bq[4], br[4];
      ldsm4(bq, bo1);
      ldsm4(br, bo1 + 64);
      const uint32_t b0 = bq[0], b1 = bq[1], b2 = bq[2], b3 = bq[3], b4 = br[0];
      if (!have_d) { mbar_wait(bars + 8 * (B_DN + (warp >> 2)), 0); load_d(); }
      float d[3][4] = {{0, 0, 0, 0}, {0, 0, 0, 0}, {0, 0, 0, 0}};
#pragma unroll
      for (int m = 0; m < 3; m++) mma16(d[m], adn[2 * m], b0, b1);
#pragma unroll
      for (int m = 0; m < 3; m++) mma16(d[m], adn[2 * m + 1], b2, b3);
      if (wide) {
#pragma unroll
        for (int m = 0; m < 3; m++) mma8(d[m], a8[m], b4);
      }
      send_pieces(G, roff, d, t, 0u);
    }
  }

  if (cta < 72) {
    uint16_t* dst = (uint16_t*)A.out + t * 576 + cta * 8 + g;
    KEEPL(dst);
    reduce_pieces(rsrc, 0u, sb, warp, lane, bars + 8 * B_GB, sb + ST_OFF + 768, sb + ST_OFF + 640, [&](float y) { *dst = to_bf16(y); });
  }
}

typedef CUresult (*EncFn)(CUtensorMap*, CUtensorMapDataType, cuuint32_t, void*, const cuuint64_t*, const cuuint64_t*,
                          const cuuint32_t*, const cuuint32_t*, CUtensorMapInterleave, CUtensorMapSwizzle,
                          CUtensorMapL2promotion, CUtensorMapFloatOOBfill);

static void make_map(EncFn f, CUtensorMap* m, void* p, uint64_t cols, uint64_t rows, uint64_t inner, uint32_t bc, uint32_t br, uint32_t bs, int swz) {
  cuuint64_t gd[3] = {inner, rows, cols / inner};
  cuuint64_t gs[2] = {cols * 2, inner * 2};
  cuuint32_t bd[3] = {bc, br, bs};
  cuuint32_t es[3] = {1, 1, 1};
  f(m, CU_TENSOR_MAP_DATA_TYPE_BFLOAT16, 3, p, gd, gs, bd, es, CU_TENSOR_MAP_INTERLEAVE_NONE,
    swz == 1 ? CU_TENSOR_MAP_SWIZZLE_128B : swz == 2 ? CU_TENSOR_MAP_SWIZZLE_64B : CU_TENSOR_MAP_SWIZZLE_NONE, CU_TENSOR_MAP_L2_PROMOTION_L2_128B,
    CU_TENSOR_MAP_FLOAT_OOB_FILL_NONE);
}

extern "C" void kernel_launch(void* const* d_in, const int* in_sizes, int n_in, void* d_out, int out_size) {
  static EncFn enc = nullptr;
  static char* box = nullptr;
  if (!enc) {
    void* fn = nullptr;
    cudaDriverEntryPointQueryResult qr;
    cudaGetDriverEntryPoint("cuTensorMapEncodeTiled", &fn, cudaEnableDefault, &qr);
    enc = (EncFn)fn;
    cudaGetSymbolAddress((void**)&box, g_box);
    box = (char*)(((uintptr_t)box + 0x1FFFFF) & ~(uintptr_t)0x1FFFFF);
    cudaFuncSetAttribute(fused_kernel, cudaFuncAttributeMaxDynamicSharedMemorySize, SMEM_BYTES);
  }
  Maps M;
  make_map(enc, &M.wq, d_in[2], 4096, 576, 64, 64, 72, 1, true);
  make_map(enc, &M.wuk, d_in[3], 4096, 512, 64, 64, 64, 1, true);
  make_map(enc, &M.ckv, d_in[1], 512, 16384, 64, 64, 64, 1, true);
  make_map(enc, &M.wuv, d_in[4], 4096, 512, 64, 64, 64, 1, true);
  make_map(enc, &M.wo, d_in[5], 576, 4096, 64, 64, 32, 3, true);
  make_map(enc, &M.gate80, d_in[7], 4608, 576, 4608, 80, 48, 1, false);
  make_map(enc, &M.up80, d_in[8], 4608, 576, 4608, 80, 48, 1, false);
  make_map(enc, &M.gate64, d_in[7], 4608, 576, 4608, 64, 48, 1, true);
  make_map(enc, &M.up64, d_in[8], 4608, 576, 4608, 64, 48, 1, true);
  make_map(enc, &M.down40, d_in[9], 576, 4608, 64, 64, 40, 3, true);
  make_map(enc, &M.down32, d_in[9], 576, 4608, 64, 64, 32, 3, true);
  make_map(enc, &M.mod2, d_in[11], 3456, 576, 3456, 144, 64, 1, false);
  make_map(enc, &M.mod1, d_in[11], 3456, 576, 3456, 32, 192, 1, 2);
  Prm A;
  A.x = (const bf16*)d_in[0];
  A.c = (const bf16*)d_in[10];
  A.out = (bf16*)d_out;
  A.box = box;
  Sched S;
  {
    const char* wins = "4444333334444444444322";
    int q4[NSTEP];
    double tm = PACE_T0;
    for (int i = 0; i < NSTEP; i++) {
      if (i == B_WUK) tm += GAP_A;
      if (i == B_WUV) tm += GAP_B;
      q4[i] = i < B_WUK ? 36 : i < B_WO ? 32 : i < B_GU ? 48 : i < B_DN ? 27 : 54;
      const int ph = i < B_CKV + SW_P ? 0 : i < B_WUV ? 1 : 2;
      const int pace = ph == 0 ? PACE_A : ph == 1 ? PACE_P : i < B_GU ? PACE_B : i < B_DN ? PACE_G : PACE_D;
      int k = i;
      if (ph == 2) k = i - (wins[i - B_WUV] - '0');
      else for (int sum = 0; k >= 0 && sum + q4[k] <= 4 * (ph ? W_P : W_A); k--) sum += q4[k];
      const int k2 = k - (ph == 0 ? XWIN_A : ph == 1 ? XWIN_P : XWIN);
      int fb = 255;
      if (i == B_CKV + 12) fb = B_QDONE;
      else if (i >= B_DN) fb = B_SC;
      else if (i >= B_GU + 8) fb = B_TFREE + 3;
      else if (i >= B_GU + 3) fb = B_TFREE + 2;
      else if (i >= B_WO + 2) fb = B_TFREE + 1;
      else if (i >= B_WO) fb = B_TFREE;
      S.e[i] = make_uint2(i | ((k >= 0 ? k : 255) << 8) | (fb << 16) | ((unsigned)(k2 >= 0 ? k2 : 255) << 24), (unsigned)tm * 0x10001u);
      tm += q4[i] * pace / 4096.0;
    }
    const double t_a = S.e[B_CKV].y & 0xFFFF, t_b = (S.e[B_WUV].y & 0xFFFF) - GAP_B, dt = (t_b - t_a) / 16, x = SKEW / 100.0;
    const double nb1 = 16 * (1 - x) / (1 + x);
    for (int c = 0; c < 16; c++) {
      const double ta = t_a + c * dt / (1 + x);
      const double tb = c <= nb1 ? t_a + c * dt / (1 - x) : t_a + 16 * dt / (1 + x) + (c - nb1) * dt / 2;
      S.e[B_CKV + c].y = (unsigned)ta | ((unsigned)tb << 16);
    }
    for (int i = NSTEP; i < 64; i++) S.e[i] = make_uint2(0, 0);
  }
  fused_kernel<<<132, NTHR, SMEM_BYTES>>>(A, M, S);
}
```
